```python
import torch

def _softmax(x, axis=-1):
    return torch.softmax(x, dim=axis)

def _gelu(x):
    return torch.nn.functional.gelu(x, approximate='tanh')

def _silu(x):
    return torch.nn.functional.silu(x)

def _sigmoid(x):
    return torch.sigmoid(x)

def _layernorm(x, axis=-1, eps=1e-05):
    m = x.mean(dim=axis, keepdim=True)
    v = x.var(dim=axis, keepdim=True, unbiased=False)
    return (x - m) / torch.sqrt(v + eps)

def _scatter_add(tgt, idx, src, axis=0):
    return tgt.clone().index_add_(axis, idx, src)

def _segment_sum(src, seg, n):
    out = torch.zeros((n,) + src.shape[1:], dtype=src.dtype)
    return out.index_add_(0, seg, src)

def _pad(x, pw):
    flat = tuple((v for pair in reversed(pw) for v in pair))
    return torch.nn.functional.pad(x, flat)
kernel_name = 'standalone__video_timesformer__vision'

def setup_inputs():

    _w = lambda a: (lambda t: t.to(torch.bfloat16) if t.is_floating_point() else t)(torch.as_tensor(a))
    T = 7
    p = 14
    HW = 512 // p * p
    N = (HW // p) ** 2
    C = 192
    return {'x': _w((lambda *s: torch.randn(*s, dtype=torch.bfloat16) * 0.1)(1, T, N, C)), 'wqkv_t': _w((lambda *s: torch.randn(*s, dtype=torch.bfloat16) * 0.1)(C, 3 * C)), 'wo_t': _w((lambda *s: torch.randn(*s, dtype=torch.bfloat16) * 0.1)(C, C)), 'wqkv_s': _w((lambda *s: torch.randn(*s, dtype=torch.bfloat16) * 0.1)(C, 3 * C)), 'wo_s': _w((lambda *s: torch.randn(*s, dtype=torch.bfloat16) * 0.8)(C, C))}

def reference(x, wqkv_t, wo_t, wqkv_s, wo_s):
    B, T, N, C = x.shape
    scale = C ** (-0.5)
    xt = (lambda x, *d: x.permute(*d))(x, 0, 2, 1, 3).reshape(B * N, T, C)
    h = _layernorm(xt, axis=-1)
    qkv = h @ wqkv_t
    q, k, v = (qkv[..., :C].clone(), qkv[..., C:2 * C].clone(), qkv[..., 2 * C:].clone())
    a = _softmax(torch.einsum('btc,bsc->bts', q, k) * scale, axis=-1)
    xt = xt + torch.einsum('bts,bsc->btc', a, v) @ wo_t
    x1 = (lambda x, *d: x.permute(*d))(xt.reshape(B, N, T, C), 0, 2, 1, 3)
    xs = x1.reshape(B * T, N, C)
    h = _layernorm(xs, axis=-1)
    qkv = h @ wqkv_s
    q, k, v = (qkv[..., :C].clone(), qkv[..., C:2 * C].clone(), qkv[..., 2 * C:].clone())
    a = _softmax(torch.einsum('bnc,bmc->bnm', q, k) * scale, axis=-1)
    xs = xs + torch.einsum('bnm,bmc->bnc', a, v) @ wo_s
    return xs.reshape(B, T, N, C)
```

```cpp
#include <cuda_runtime.h>
#include <cuda_bf16.h>
#include <stdint.h>

namespace tsf {

constexpr int T_ = 7, N_ = 1296, C_ = 192, ROWS = T_ * N_;
constexpr float SM_SCALE_LOG2 = 0.07216878364870322f * 1.4426950408889634f;
constexpr uint32_t SPIN_LIMIT = 1u << 24;

__device__ __align__(1024) __nv_bfloat16 g_w[4 * 3 * 192 * 64];
__device__ __align__(1024) __nv_bfloat16 g_x1[ROWS * C_];
__device__ __align__(1024) __nv_bfloat16 g_h2[T_ * 3 * N_ * 64];
__device__ __align__(1024) __nv_bfloat16 g_q2[T_ * 3 * N_ * 64 + 64 * 64];
__device__ __align__(1024) float g_pL[T_ * 9 * 128 * 192];
__device__ float g_mL[T_ * 9 * 128], g_lL[T_ * 9 * 128];
__device__ __align__(1024) float g_pU[12 * 2 * 16 * 192];
__device__ float g_mU[12 * 2 * 16], g_lU[12 * 2 * 16];
__device__ unsigned int g_cnt[16];

__device__ __forceinline__ uint32_t smem_u32(const void* p) { return (uint32_t)__cvta_generic_to_shared(p); }
__device__ __forceinline__ void mbar_init(uint32_t bar, uint32_t count) {
  asm volatile("mbarrier.init.shared::cta.b64 [%0], %1;" ::"r"(bar), "r"(count) : "memory");
}
__device__ __forceinline__ void mbar_expect_tx(uint32_t bar, uint32_t bytes) {
  asm volatile("mbarrier.arrive.expect_tx.shared::cta.b64 _, [%0], %1;" ::"r"(bar), "r"(bytes) : "memory");
}
__device__ __forceinline__ void mbar_arrive(uint32_t bar) {
  asm volatile("mbarrier.arrive.shared::cta.b64 _, [%0];" ::"r"(bar) : "memory");
}
__device__ __forceinline__ void mbar_arrive_remote(uint32_t rbar) {
  asm volatile("mbarrier.arrive.release.cluster.shared::cluster.b64 _, [%0];" ::"r"(rbar) : "memory");
}
__device__ __forceinline__ bool mbar_try(uint32_t bar, uint32_t parity) {
  uint32_t ok;
  asm volatile("{\n.reg .pred p;\nmbarrier.try_wait.parity.shared::cta.b64 p, [%1], %2;\nselp.u32 %0, 1, 0, p;\n}\n"
               : "=r"(ok) : "r"(bar), "r"(parity) : "memory");
  return ok != 0;
}
__device__ __forceinline__ bool mbar_try_cluster(uint32_t bar, uint32_t parity) {
  uint32_t ok;
  asm volatile("{\n.reg .pred p;\nmbarrier.try_wait.parity.acquire.cluster.shared::cta.b64 p, [%1], %2;\nselp.u32 %0, 1, 0, p;\n}\n"
               : "=r"(ok) : "r"(bar), "r"(parity) : "memory");
  return ok != 0;
}
__device__ __forceinline__ void mbar_wait(uint32_t bar, uint32_t parity) {
  for (uint32_t it = 0; it < SPIN_LIMIT; ++it)
    if (mbar_try(bar, parity)) return;
  __trap();
}
__device__ __forceinline__ void mbar_wait_cluster(uint32_t bar, uint32_t parity) {
  for (uint32_t it = 0; it < SPIN_LIMIT; ++it)
    if (mbar_try_cluster(bar, parity)) return;
  __trap();
}
__device__ __forceinline__ void bulk_g2s(uint32_t dst, const void* src, uint32_t bytes, uint32_t bar) {
  asm volatile("cp.async.bulk.shared::cluster.global.mbarrier::complete_tx::bytes [%0], [%1], %2, [%3];"
               ::"r"(dst), "l"(src), "r"(bytes), "r"(bar) : "memory");
}
__device__ __forceinline__ void fence_async_smem() { asm volatile("fence.proxy.async.shared::cta;" ::: "memory"); }
__device__ __forceinline__ void fence_mbar_init() { asm volatile("fence.mbarrier_init.release.cluster;" ::: "memory"); }
__device__ __forceinline__ void named_bar(int id, int n) { asm volatile("bar.sync %0, %1;" ::"r"(id), "r"(n) : "memory"); }
__device__ __forceinline__ void wg_fence() { asm volatile("wgmma.fence.sync.aligned;" ::: "memory"); }
__device__ __forceinline__ void wg_commit() { asm volatile("wgmma.commit_group.sync.aligned;" ::: "memory"); }
template <int N> __device__ __forceinline__ void wg_wait() { asm volatile("wgmma.wait_group.sync.aligned %0;" ::"n"(N) : "memory"); }
template <int N> __device__ __forceinline__ void fence_regs(float (&d)[N]) {
#pragma unroll
  for (int i = 0; i < N; ++i) asm volatile("" : "+f"(d[i])::"memory");
}
__device__ __forceinline__ void pdl_wait() { asm volatile("griddepcontrol.wait;" ::: "memory"); }
__device__ __forceinline__ void pdl_launch() { asm volatile("griddepcontrol.launch_dependents;" ::: "memory"); }
__device__ __forceinline__ uint32_t mapa(uint32_t addr, uint32_t rank) {
  uint32_t r;
  asm volatile("mapa.shared::cluster.u32 %0, %1, %2;" : "=r"(r) : "r"(addr), "r"(rank));
  return r;
}
__device__ __forceinline__ void cluster_sync_all() {
  asm volatile("barrier.cluster.arrive.release.aligned;\nbarrier.cluster.wait.acquire.aligned;" ::: "memory");
}
__device__ __forceinline__ void st_cluster_v4(uint32_t addr, float a, float b, float c, float d) {
  asm volatile("st.shared::cluster.v4.f32 [%0], {%1, %2, %3, %4};" ::"r"(addr), "f"(a), "f"(b), "f"(c), "f"(d) : "memory");
}
__device__ __forceinline__ uint64_t make_desc(uint32_t addr, uint32_t lbo, uint32_t sbo) {
  return (uint64_t)((addr & 0x3FFFF) >> 4) | ((uint64_t)(lbo >> 4) << 16) | ((uint64_t)(sbo >> 4) << 32) | (1ull << 62);
}
__device__ __forceinline__ uint32_t pack_bf16(float lo, float hi) {
  uint32_t r;
  asm("cvt.rn.bf16x2.f32 %0, %1, %2;" : "=r"(r) : "f"(hi), "f"(lo));
  return r;
}
__device__ __forceinline__ float bf_lo(uint32_t v) { return __uint_as_float(v << 16); }
__device__ __forceinline__ float bf_hi(uint32_t v) { return __uint_as_float(v & 0xffff0000u); }
__device__ __forceinline__ float ex2(float x) {
  float r;
  asm("ex2.approx.ftz.f32 %0, %1;" : "=f"(r) : "f"(x));
  return r;
}
__device__ __forceinline__ int swz(int row, int col) { return row * 64 + ((((col >> 3) ^ row) & 7) << 3) + (col & 7); }

template <int TB>
__device__ __forceinline__ void wgmma_ss_n192(float (&d)[96], uint64_t da, uint64_t db, int sc) {
  asm volatile("{\n.reg .pred p;\nsetp.ne.b32 p, %98, 0;\n"
    "wgmma.mma_async.sync.aligned.m64n192k16.f32.bf16.bf16 "
    "{%0, %1, %2, %3, %4, %5, %6, %7, %8, %9, %10, %11, %12, %13, %14, %15, %16, %17, %18, %19, %20, %21, %22, %23, %24, %25, %26, %27, %28, %29, %30, %31, %32, %33, %34, %35, %36, %37, %38, %39, %40, %41, %42, %43, %44, %45, %46, %47, %48, %49, %50, %51, %52, %53, %54, %55, %56, %57, %58, %59, %60, %61, %62, %63, %64, %65, %66, %67, %68, %69, %70, %71, %72, %73, %74, %75, %76, %77, %78, %79, %80, %81, %82, %83, %84, %85, %86, %87, %88, %89, %90, %91, %92, %93, %94, %95}, "
    "%96, %97, p, 1, 1, 0, %99;\n}\n"
    : "+f"(d[0]), "+f"(d[1]), "+f"(d[2]), "+f"(d[3]), "+f"(d[4]), "+f"(d[5]), "+f"(d[6]), "+f"(d[7]), "+f"(d[8]), "+f"(d[9]), "+f"(d[10]), "+f"(d[11]), "+f"(d[12]), "+f"(d[13]), "+f"(d[14]), "+f"(d[15]), "+f"(d[16]), "+f"(d[17]), "+f"(d[18]), "+f"(d[19]), "+f"(d[20]), "+f"(d[21]), "+f"(d[22]), "+f"(d[23]), "+f"(d[24]), "+f"(d[25]), "+f"(d[26]), "+f"(d[27]), "+f"(d[28]), "+f"(d[29]), "+f"(d[30]), "+f"(d[31]), "+f"(d[32]), "+f"(d[33]), "+f"(d[34]), "+f"(d[35]), "+f"(d[36]), "+f"(d[37]), "+f"(d[38]), "+f"(d[39]), "+f"(d[40]), "+f"(d[41]), "+f"(d[42]), "+f"(d[43]), "+f"(d[44]), "+f"(d[45]), "+f"(d[46]), "+f"(d[47]), "+f"(d[48]), "+f"(d[49]), "+f"(d[50]), "+f"(d[51]), "+f"(d[52]), "+f"(d[53]), "+f"(d[54]), "+f"(d[55]), "+f"(d[56]), "+f"(d[57]), "+f"(d[58]), "+f"(d[59]), "+f"(d[60]), "+f"(d[61]), "+f"(d[62]), "+f"(d[63]), "+f"(d[64]), "+f"(d[65]), "+f"(d[66]), "+f"(d[67]), "+f"(d[68]), "+f"(d[69]), "+f"(d[70]), "+f"(d[71]), "+f"(d[72]), "+f"(d[73]), "+f"(d[74]), "+f"(d[75]), "+f"(d[76]), "+f"(d[77]), "+f"(d[78]), "+f"(d[79]), "+f"(d[80]), "+f"(d[81]), "+f"(d[82]), "+f"(d[83]), "+f"(d[84]), "+f"(d[85]), "+f"(d[86]), "+f"(d[87]), "+f"(d[88]), "+f"(d[89]), "+f"(d[90]), "+f"(d[91]), "+f"(d[92]), "+f"(d[93]), "+f"(d[94]), "+f"(d[95])
    : "l"(da), "l"(db), "r"(sc), "n"(TB));
}
template <int TB>
__device__ __forceinline__ void wgmma_rs_n192(float (&d)[96], uint32_t a0, uint32_t a1, uint32_t a2, uint32_t a3, uint64_t db, int sc) {
  asm volatile("{\n.reg .pred p;\nsetp.ne.b32 p, %101, 0;\n"
    "wgmma.mma_async.sync.aligned.m64n192k16.f32.bf16.bf16 "
    "{%0, %1, %2, %3, %4, %5, %6, %7, %8, %9, %10, %11, %12, %13, %14, %15, %16, %17, %18, %19, %20, %21, %22, %23, %24, %25, %26, %27, %28, %29, %30, %31, %32, %33, %34, %35, %36, %37, %38, %39, %40, %41, %42, %43, %44, %45, %46, %47, %48, %49, %50, %51, %52, %53, %54, %55, %56, %57, %58, %59, %60, %61, %62, %63, %64, %65, %66, %67, %68, %69, %70, %71, %72, %73, %74, %75, %76, %77, %78, %79, %80, %81, %82, %83, %84, %85, %86, %87, %88, %89, %90, %91, %92, %93, %94, %95}, "
    "{%96, %97, %98, %99}, %100, p, 1, 1, %102;\n}\n"
    : "+f"(d[0]), "+f"(d[1]), "+f"(d[2]), "+f"(d[3]), "+f"(d[4]), "+f"(d[5]), "+f"(d[6]), "+f"(d[7]), "+f"(d[8]), "+f"(d[9]), "+f"(d[10]), "+f"(d[11]), "+f"(d[12]), "+f"(d[13]), "+f"(d[14]), "+f"(d[15]), "+f"(d[16]), "+f"(d[17]), "+f"(d[18]), "+f"(d[19]), "+f"(d[20]), "+f"(d[21]), "+f"(d[22]), "+f"(d[23]), "+f"(d[24]), "+f"(d[25]), "+f"(d[26]), "+f"(d[27]), "+f"(d[28]), "+f"(d[29]), "+f"(d[30]), "+f"(d[31]), "+f"(d[32]), "+f"(d[33]), "+f"(d[34]), "+f"(d[35]), "+f"(d[36]), "+f"(d[37]), "+f"(d[38]), "+f"(d[39]), "+f"(d[40]), "+f"(d[41]), "+f"(d[42]), "+f"(d[43]), "+f"(d[44]), "+f"(d[45]), "+f"(d[46]), "+f"(d[47]), "+f"(d[48]), "+f"(d[49]), "+f"(d[50]), "+f"(d[51]), "+f"(d[52]), "+f"(d[53]), "+f"(d[54]), "+f"(d[55]), "+f"(d[56]), "+f"(d[57]), "+f"(d[58]), "+f"(d[59]), "+f"(d[60]), "+f"(d[61]), "+f"(d[62]), "+f"(d[63]), "+f"(d[64]), "+f"(d[65]), "+f"(d[66]), "+f"(d[67]), "+f"(d[68]), "+f"(d[69]), "+f"(d[70]), "+f"(d[71]), "+f"(d[72]), "+f"(d[73]), "+f"(d[74]), "+f"(d[75]), "+f"(d[76]), "+f"(d[77]), "+f"(d[78]), "+f"(d[79]), "+f"(d[80]), "+f"(d[81]), "+f"(d[82]), "+f"(d[83]), "+f"(d[84]), "+f"(d[85]), "+f"(d[86]), "+f"(d[87]), "+f"(d[88]), "+f"(d[89]), "+f"(d[90]), "+f"(d[91]), "+f"(d[92]), "+f"(d[93]), "+f"(d[94]), "+f"(d[95])
    : "r"(a0), "r"(a1), "r"(a2), "r"(a3), "l"(db), "r"(sc), "n"(TB));
}
template <int TB>
__device__ __forceinline__ void wgmma_rs_n64(float (&d)[32], uint32_t a0, uint32_t a1, uint32_t a2, uint32_t a3, uint64_t db, int sc) {
  asm volatile("{\n.reg .pred p;\nsetp.ne.b32 p, %37, 0;\n"
    "wgmma.mma_async.sync.aligned.m64n64k16.f32.bf16.bf16 "
    "{%0, %1, %2, %3, %4, %5, %6, %7, %8, %9, %10, %11, %12, %13, %14, %15, %16, %17, %18, %19, %20, %21, %22, %23, %24, %25, %26, %27, %28, %29, %30, %31}, "
    "{%32, %33, %34, %35}, %36, p, 1, 1, %38;\n}\n"
    : "+f"(d[0]), "+f"(d[1]), "+f"(d[2]), "+f"(d[3]), "+f"(d[4]), "+f"(d[5]), "+f"(d[6]), "+f"(d[7]), "+f"(d[8]), "+f"(d[9]), "+f"(d[10]), "+f"(d[11]), "+f"(d[12]), "+f"(d[13]), "+f"(d[14]), "+f"(d[15]), "+f"(d[16]), "+f"(d[17]), "+f"(d[18]), "+f"(d[19]), "+f"(d[20]), "+f"(d[21]), "+f"(d[22]), "+f"(d[23]), "+f"(d[24]), "+f"(d[25]), "+f"(d[26]), "+f"(d[27]), "+f"(d[28]), "+f"(d[29]), "+f"(d[30]), "+f"(d[31])
    : "r"(a0), "r"(a1), "r"(a2), "r"(a3), "l"(db), "r"(sc), "n"(TB));
}
template <int TB>
__device__ __forceinline__ void wgmma_ss_n144(float (&d)[72], uint64_t da, uint64_t db, int sc) {
  asm volatile("{\n.reg .pred p;\nsetp.ne.b32 p, %74, 0;\n"
    "wgmma.mma_async.sync.aligned.m64n144k16.f32.bf16.bf16 "
    "{%0, %1, %2, %3, %4, %5, %6, %7, %8, %9, %10, %11, %12, %13, %14, %15, %16, %17, %18, %19, %20, %21, %22, %23, %24, %25, %26, %27, %28, %29, %30, %31, %32, %33, %34, %35, %36, %37, %38, %39, %40, %41, %42, %43, %44, %45, %46, %47, %48, %49, %50, %51, %52, %53, %54, %55, %56, %57, %58, %59, %60, %61, %62, %63, %64, %65, %66, %67, %68, %69, %70, %71}, "
    "%72, %73, p, 1, 1, 0, %75;\n}\n"
    : "+f"(d[0]), "+f"(d[1]), "+f"(d[2]), "+f"(d[3]), "+f"(d[4]), "+f"(d[5]), "+f"(d[6]), "+f"(d[7]), "+f"(d[8]), "+f"(d[9]), "+f"(d[10]), "+f"(d[11]), "+f"(d[12]), "+f"(d[13]), "+f"(d[14]), "+f"(d[15]), "+f"(d[16]), "+f"(d[17]), "+f"(d[18]), "+f"(d[19]), "+f"(d[20]), "+f"(d[21]), "+f"(d[22]), "+f"(d[23]), "+f"(d[24]), "+f"(d[25]), "+f"(d[26]), "+f"(d[27]), "+f"(d[28]), "+f"(d[29]), "+f"(d[30]), "+f"(d[31]), "+f"(d[32]), "+f"(d[33]), "+f"(d[34]), "+f"(d[35]), "+f"(d[36]), "+f"(d[37]), "+f"(d[38]), "+f"(d[39]), "+f"(d[40]), "+f"(d[41]), "+f"(d[42]), "+f"(d[43]), "+f"(d[44]), "+f"(d[45]), "+f"(d[46]), "+f"(d[47]), "+f"(d[48]), "+f"(d[49]), "+f"(d[50]), "+f"(d[51]), "+f"(d[52]), "+f"(d[53]), "+f"(d[54]), "+f"(d[55]), "+f"(d[56]), "+f"(d[57]), "+f"(d[58]), "+f"(d[59]), "+f"(d[60]), "+f"(d[61]), "+f"(d[62]), "+f"(d[63]), "+f"(d[64]), "+f"(d[65]), "+f"(d[66]), "+f"(d[67]), "+f"(d[68]), "+f"(d[69]), "+f"(d[70]), "+f"(d[71])
    : "l"(da), "l"(db), "r"(sc), "n"(TB));
}


__global__ void __launch_bounds__(128) p0_kernel(const __nv_bfloat16* __restrict__ wqkv_t, const __nv_bfloat16* __restrict__ wo_t,
                                                 const __nv_bfloat16* __restrict__ wqkv_s, const __nv_bfloat16* __restrict__ wo_s) {
  pdl_launch();
  if (blockIdx.x == 0 && threadIdx.x < 16) g_cnt[threadIdx.x] = 0;
  const int gw = blockIdx.x * 4 + (threadIdx.x >> 5);
  const int lane = threadIdx.x & 31;
  const int m = gw / 144, tile = gw % 144;
  const int n0 = (tile / 12) * 16, k0 = (tile % 12) * 16;
  const __nv_bfloat16* wqkv = (m < 2) ? wqkv_t : wqkv_s;
  const __nv_bfloat16* wo = (m < 2) ? wo_t : wo_s;
  const int g = lane >> 2, q = lane & 3;
  float acc[2][4] = {};
  const unsigned short* wo16 = reinterpret_cast<const unsigned short*>(wo);
#pragma unroll 4
  for (int c0 = 0; c0 < 192; c0 += 16) {
    uint32_t a[4];
    if ((m & 1) == 0) {
      const __nv_bfloat16* r0 = wqkv + (size_t)(n0 + g) * 576 + 192 + c0 + 2 * q;
      const __nv_bfloat16* r1 = r0 + 8 * 576;
      a[0] = *reinterpret_cast<const uint32_t*>(r0);
      a[1] = *reinterpret_cast<const uint32_t*>(r1);
      a[2] = *reinterpret_cast<const uint32_t*>(r0 + 8);
      a[3] = *reinterpret_cast<const uint32_t*>(r1 + 8);
    } else {
      const int c = c0 + 2 * q;
      a[0] = (uint32_t)wo16[c * 192 + n0 + g] | ((uint32_t)wo16[(c + 1) * 192 + n0 + g] << 16);
      a[1] = (uint32_t)wo16[c * 192 + n0 + g + 8] | ((uint32_t)wo16[(c + 1) * 192 + n0 + g + 8] << 16);
      a[2] = (uint32_t)wo16[(c + 8) * 192 + n0 + g] | ((uint32_t)wo16[(c + 9) * 192 + n0 + g] << 16);
      a[3] = (uint32_t)wo16[(c + 8) * 192 + n0 + g + 8] | ((uint32_t)wo16[(c + 9) * 192 + n0 + g + 8] << 16);
    }
    const int boff = (m & 1) ? 384 : 0;
#pragma unroll
    for (int j = 0; j < 2; ++j) {
      const __nv_bfloat16* rb = wqkv + (size_t)(k0 + 8 * j + g) * 576 + boff + c0 + 2 * q;
      uint32_t b0 = *reinterpret_cast<const uint32_t*>(rb);
      uint32_t b1 = *reinterpret_cast<const uint32_t*>(rb + 8);
      asm volatile("mma.sync.aligned.m16n8k16.row.col.f32.bf16.bf16.f32 {%0,%1,%2,%3}, {%4,%5,%6,%7}, {%8,%9}, {%0,%1,%2,%3};"
                   : "+f"(acc[j][0]), "+f"(acc[j][1]), "+f"(acc[j][2]), "+f"(acc[j][3])
                   : "r"(a[0]), "r"(a[1]), "r"(a[2]), "r"(a[3]), "r"(b0), "r"(b1));
    }
  }
  __nv_bfloat16* dst = g_w + (size_t)m * 3 * 192 * 64;
#pragma unroll
  for (int j = 0; j < 2; ++j) {
    const int k = k0 + 8 * j + 2 * q;
    __nv_bfloat16* ch = dst + (k >> 6) * (192 * 64);
    *reinterpret_cast<uint32_t*>(ch + swz(n0 + g, k & 63)) = pack_bf16(acc[j][0], acc[j][1]);
    *reinterpret_cast<uint32_t*>(ch + swz(n0 + g + 8, k & 63)) = pack_bf16(acc[j][2], acc[j][3]);
  }
}

constexpr int W_BYTES = 3 * 192 * 128;
constexpr int WCH = 192 * 128;
constexpr int TILE_BYTES = 3 * 64 * 128;
constexpr int P1_SMEM = 2 * W_BYTES + 2 * TILE_BYTES + 64 + 1024;

__device__ __forceinline__ void gemm_rs_w(float (&acc)[96], const uint32_t (&a)[48], uint32_t c0, uint32_t c1, uint32_t c2) {
  wg_fence();
#pragma unroll
  for (int kk = 0; kk < 12; ++kk) {
    const uint32_t base = (kk < 4) ? c0 : ((kk < 8) ? c1 : c2);
    wgmma_rs_n192<0>(acc, a[4 * kk], a[4 * kk + 1], a[4 * kk + 2], a[4 * kk + 3], make_desc(base + (kk & 3) * 32, 16, 1024), kk > 0);
  }
  wg_commit();
}
__device__ __forceinline__ void gemm_ss_w(float (&acc)[96], uint32_t atile, uint32_t c0, uint32_t c1, uint32_t c2) {
  wg_fence();
#pragma unroll
  for (int kk = 0; kk < 12; ++kk) {
    const uint32_t base = (kk < 4) ? c0 : ((kk < 8) ? c1 : c2);
    wgmma_ss_n192<0>(acc, make_desc(atile + (kk >> 2) * 8192 + (kk & 3) * 32, 16, 1024), make_desc(base + (kk & 3) * 32, 16, 1024), kk > 0);
  }
  wg_commit();
}

__global__ void __launch_bounds__(384, 1) p1_kernel(const __nv_bfloat16* __restrict__ x) {
  extern __shared__ uint8_t smem_raw[];
  const uint32_t sbase = (smem_u32(smem_raw) + 1023) & ~1023u;
  uint8_t* sptr = smem_raw + (sbase - smem_u32(smem_raw));
  const uint32_t sWA = sbase, sWB = sbase + W_BYTES, sH = sbase + 2 * W_BYTES;
  const uint32_t bars = sH + 2 * TILE_BYTES;
  const int tid = threadIdx.x, warp = tid >> 5, lane = tid & 31;
  pdl_launch();
  if (tid == 0) {
    mbar_init(bars, 1); mbar_init(bars + 8, 1); mbar_init(bars + 16, 1); mbar_init(bars + 24, 8);
    fence_mbar_init();
  }
  __syncthreads();

  if (warp >= 8) {
    asm volatile("setmaxnreg.dec.sync.aligned.u32 40;");
    if (warp == 8 && lane == 0) {
      pdl_wait();
      mbar_expect_tx(bars, W_BYTES);
      bulk_g2s(sWA, g_w, W_BYTES, bars);
      mbar_expect_tx(bars + 8, W_BYTES);
      bulk_g2s(sWB, g_w + 3 * 192 * 64, W_BYTES, bars + 8);
      mbar_wait(bars + 24, 0);
      mbar_expect_tx(bars + 16, W_BYTES);
      bulk_g2s(sWA, g_w + 2 * 3 * 192 * 64, W_BYTES, bars + 16);
    }
    return;
  }

  asm volatile("setmaxnreg.inc.sync.aligned.u32 232;");
  const int wg = warp >> 2, t = tid & 127, wl = warp & 3;
  const int n0 = (blockIdx.x * 2 + wg) * 9;
  const uint32_t sHt = sH + wg * TILE_BYTES;
  uint8_t* pHt = sptr + 2 * W_BYTES + wg * TILE_BYTES;
  {
    const int row = t >> 1, half = t & 1;
    uint4 v[12];
    if (row < 63) {
      const int j = row / 7, tt = row - j * 7;
      const uint4* src = reinterpret_cast<const uint4*>(x + ((size_t)tt * N_ + n0 + j) * C_ + half * 96);
#pragma unroll
      for (int i = 0; i < 12; ++i) v[i] = __ldg(src + i);
    } else {
#pragma unroll
      for (int i = 0; i < 12; ++i) v[i] = make_uint4(0, 0, 0, 0);
    }
    float s = 0.f;
#pragma unroll
    for (int i = 0; i < 12; ++i) {
      s += bf_lo(v[i].x) + bf_hi(v[i].x) + bf_lo(v[i].y) + bf_hi(v[i].y) + bf_lo(v[i].z) + bf_hi(v[i].z) + bf_lo(v[i].w) + bf_hi(v[i].w);
    }
    s += __shfl_xor_sync(0xffffffffu, s, 1);
    const float mean = s * (1.f / 192.f);
    float ss = 0.f;
#pragma unroll
    for (int i = 0; i < 12; ++i) {
      const uint32_t w4[4] = {v[i].x, v[i].y, v[i].z, v[i].w};
#pragma unroll
      for (int e = 0; e < 4; ++e) {
        float a = bf_lo(w4[e]) - mean, b = bf_hi(w4[e]) - mean;
        ss += a * a + b * b;
      }
    }
    ss += __shfl_xor_sync(0xffffffffu, ss, 1);
    const float rstd = 1.f / sqrtf(ss * (1.f / 192.f) + 1e-5f);
#pragma unroll
    for (int i = 0; i < 12; ++i) {
      const uint32_t w4[4] = {v[i].x, v[i].y, v[i].z, v[i].w};
      uint32_t o4[4];
#pragma unroll
      for (int e = 0; e < 4; ++e) o4[e] = pack_bf16((bf_lo(w4[e]) - mean) * rstd, (bf_hi(w4[e]) - mean) * rstd);
      const int col = half * 96 + i * 8;
      *reinterpret_cast<uint4*>(pHt + (col >> 6) * 8192 + row * 128 + ((((col >> 3) ^ row) & 7) << 4)) = make_uint4(o4[0], o4[1], o4[2], o4[3]);
    }
  }
  fence_async_smem();
  named_bar(1 + wg, 128);

  const int g = lane >> 2, q = lane & 3;
  const int r0 = wl * 16 + g, r1 = r0 + 8;
  float acc[96];
  uint32_t af[48];
  mbar_wait(bars, 0);
  gemm_ss_w(acc, sHt, sWA, sWA + WCH, sWA + 2 * WCH);
  wg_wait<0>();
  fence_regs(acc);
  if (lane == 0) mbar_arrive(bars + 24);
#pragma unroll
  for (int i = 0; i < 48; ++i) af[i] = pack_bf16(acc[2 * i], acc[2 * i + 1]);
  float sc[32];
  wg_fence();
#pragma unroll
  for (int kk = 0; kk < 12; ++kk)
    wgmma_rs_n64<0>(sc, af[4 * kk], af[4 * kk + 1], af[4 * kk + 2], af[4 * kk + 3],
                    make_desc(sHt + (kk >> 2) * 8192 + (kk & 3) * 32, 16, 1024), kk > 0);
  wg_commit();
  wg_wait<0>();
  fence_regs(sc);
  uint32_t pf[16];
  {
    const int g0 = r0 / 7, g1 = r1 / 7;
    float mx0 = -INFINITY, mx1 = -INFINITY;
#pragma unroll
    for (int j = 0; j < 8; ++j) {
#pragma unroll
      for (int e = 0; e < 2; ++e) {
        const int col = 8 * j + 2 * q + e;
        const int cg = col / 7;
        if (cg != g0) sc[4 * j + e] = -INFINITY;
        if (cg != g1) sc[4 * j + 2 + e] = -INFINITY;
        mx0 = fmaxf(mx0, sc[4 * j + e]);
        mx1 = fmaxf(mx1, sc[4 * j + 2 + e]);
      }
    }
    mx0 = fmaxf(mx0, __shfl_xor_sync(0xffffffffu, mx0, 1)); mx0 = fmaxf(mx0, __shfl_xor_sync(0xffffffffu, mx0, 2));
    mx1 = fmaxf(mx1, __shfl_xor_sync(0xffffffffu, mx1, 1)); mx1 = fmaxf(mx1, __shfl_xor_sync(0xffffffffu, mx1, 2));
    float l0 = 0.f, l1 = 0.f;
#pragma unroll
    for (int j = 0; j < 8; ++j) {
#pragma unroll
      for (int e = 0; e < 2; ++e) {
        sc[4 * j + e] = ex2((sc[4 * j + e] - mx0) * SM_SCALE_LOG2);
        sc[4 * j + 2 + e] = ex2((sc[4 * j + 2 + e] - mx1) * SM_SCALE_LOG2);
        l0 += sc[4 * j + e];
        l1 += sc[4 * j + 2 + e];
      }
    }
    l0 += __shfl_xor_sync(0xffffffffu, l0, 1); l0 += __shfl_xor_sync(0xffffffffu, l0, 2);
    l1 += __shfl_xor_sync(0xffffffffu, l1, 1); l1 += __shfl_xor_sync(0xffffffffu, l1, 2);
    const float i0 = 1.f / l0, i1 = 1.f / l1;
#pragma unroll
    for (int j = 0; j < 8; ++j) {
      pf[2 * j] = pack_bf16(sc[4 * j] * i0, sc[4 * j + 1] * i0);
      pf[2 * j + 1] = pack_bf16(sc[4 * j + 2] * i1, sc[4 * j + 3] * i1);
    }
  }
  wg_fence();
#pragma unroll
  for (int kk = 0; kk < 4; ++kk)
    wgmma_rs_n192<1>(acc, pf[4 * kk], pf[4 * kk + 1], pf[4 * kk + 2], pf[4 * kk + 3], make_desc(sHt + kk * 2048, 8192, 1024), kk > 0);
  wg_commit();
  wg_wait<0>();
  fence_regs(acc);
#pragma unroll
  for (int i = 0; i < 48; ++i) af[i] = pack_bf16(acc[2 * i], acc[2 * i + 1]);
  mbar_wait(bars + 8, 0);
  gemm_rs_w(acc, af, sWB, sWB + WCH, sWB + 2 * WCH);
  const int j0 = r0 / 7, t0 = r0 - j0 * 7, j1 = r1 / 7, t1 = r1 - j1 * 7;
  const bool v1 = r1 < 63;
  const size_t grow0 = (size_t)t0 * N_ + n0 + j0, grow1 = v1 ? ((size_t)t1 * N_ + n0 + j1) : grow0;
  uint32_t xr[48];
  {
    const uint32_t* p0 = reinterpret_cast<const uint32_t*>(x + grow0 * C_) + q;
    const uint32_t* p1 = reinterpret_cast<const uint32_t*>(x + grow1 * C_) + q;
#pragma unroll
    for (int j = 0; j < 24; ++j) { xr[2 * j] = __ldg(p0 + 4 * j); xr[2 * j + 1] = __ldg(p1 + 4 * j); }
  }
  wg_wait<0>();
  fence_regs(acc);
  {
    float s0 = 0.f, s1 = 0.f;
    uint32_t* o0 = reinterpret_cast<uint32_t*>(g_x1 + grow0 * C_) + q;
    uint32_t* o1 = reinterpret_cast<uint32_t*>(g_x1 + grow1 * C_) + q;
#pragma unroll
    for (int j = 0; j < 24; ++j) {
      const uint32_t a = pack_bf16(bf_lo(xr[2 * j]) + acc[4 * j], bf_hi(xr[2 * j]) + acc[4 * j + 1]);
      const uint32_t b = pack_bf16(bf_lo(xr[2 * j + 1]) + acc[4 * j + 2], bf_hi(xr[2 * j + 1]) + acc[4 * j + 3]);
      o0[4 * j] = a;
      if (v1) o1[4 * j] = b;
      acc[4 * j] = bf_lo(a); acc[4 * j + 1] = bf_hi(a); acc[4 * j + 2] = bf_lo(b); acc[4 * j + 3] = bf_hi(b);
      s0 += acc[4 * j] + acc[4 * j + 1];
      s1 += acc[4 * j + 2] + acc[4 * j + 3];
    }
    s0 += __shfl_xor_sync(0xffffffffu, s0, 1); s0 += __shfl_xor_sync(0xffffffffu, s0, 2);
    s1 += __shfl_xor_sync(0xffffffffu, s1, 1); s1 += __shfl_xor_sync(0xffffffffu, s1, 2);
    const float mean0 = s0 * (1.f / 192.f), mean1 = s1 * (1.f / 192.f);
    float q0 = 0.f, q1 = 0.f;
#pragma unroll
    for (int j = 0; j < 24; ++j) {
      acc[4 * j] -= mean0; acc[4 * j + 1] -= mean0; acc[4 * j + 2] -= mean1; acc[4 * j + 3] -= mean1;
      q0 += acc[4 * j] * acc[4 * j] + acc[4 * j + 1] * acc[4 * j + 1];
      q1 += acc[4 * j + 2] * acc[4 * j + 2] + acc[4 * j + 3] * acc[4 * j + 3];
    }
    q0 += __shfl_xor_sync(0xffffffffu, q0, 1); q0 += __shfl_xor_sync(0xffffffffu, q0, 2);
    q1 += __shfl_xor_sync(0xffffffffu, q1, 1); q1 += __shfl_xor_sync(0xffffffffu, q1, 2);
    const float rs0 = 1.f / sqrtf(q0 * (1.f / 192.f) + 1e-5f), rs1 = 1.f / sqrtf(q1 * (1.f / 192.f) + 1e-5f);
#pragma unroll
    for (int j = 0; j < 24; ++j) {
      af[2 * j] = pack_bf16(acc[4 * j] * rs0, acc[4 * j + 1] * rs0);
      af[2 * j + 1] = pack_bf16(acc[4 * j + 2] * rs1, acc[4 * j + 3] * rs1);
    }
  }
  mbar_wait(bars + 16, 0);
  gemm_rs_w(acc, af, sWA, sWA + WCH, sWA + 2 * WCH);
  const int nn0 = n0 + j0, nn1 = n0 + j1;
  {
#pragma unroll
    for (int j = 0; j < 24; ++j) {
      const int ch = j >> 3, col = (j & 7) * 8 + 2 * q;
      *reinterpret_cast<uint32_t*>(g_h2 + (size_t)(t0 * 3 + ch) * (N_ * 64) + swz(nn0, col)) = af[2 * j];
      if (v1) *reinterpret_cast<uint32_t*>(g_h2 + (size_t)(t1 * 3 + ch) * (N_ * 64) + swz(nn1, col)) = af[2 * j + 1];
    }
  }
  wg_wait<0>();
  fence_regs(acc);
#pragma unroll
  for (int j = 0; j < 24; ++j) {
    const int ch = j >> 3, col = (j & 7) * 8 + 2 * q;
    *reinterpret_cast<uint32_t*>(g_q2 + (size_t)(t0 * 3 + ch) * (N_ * 64) + swz(nn0, col)) = pack_bf16(acc[4 * j], acc[4 * j + 1]);
    if (v1) *reinterpret_cast<uint32_t*>(g_q2 + (size_t)(t1 * 3 + ch) * (N_ * 64) + swz(nn1, col)) = pack_bf16(acc[4 * j + 2], acc[4 * j + 3]);
  }
}

constexpr int KB = 144;
constexpr int KCH = KB * 128;
constexpr int STAGE_BYTES = 3 * KCH;
constexpr int NSTAGE = 3;
constexpr int P2_Q_OFF = NSTAGE * STAGE_BYTES;
constexpr int P2_ML_OFF = P2_Q_OFF + 2 * TILE_BYTES;
constexpr int P2_BAR_OFF = P2_ML_OFF + 2048;
constexpr int P2_SMEM = P2_BAR_OFF + 128 + 1024;
enum { K_EXCH = 0, K_PART_L = 1, K_PART_U = 2 };

struct Seg { int f, qrow, blk0, nblk, kind, slot; };

__device__ __forceinline__ int u_lo(int u) { return (63 * u) / 12; }
__device__ __forceinline__ int num_segs(int cl, int rank, int w) {
  if (cl < 63) return rank == 0 ? 1 : 2;
  const int u = ((cl - 63) * 2 + rank) * 2 + w;
  const int lo = u_lo(u), hi = u_lo(u + 1);
  return (lo / 9 == (hi - 1) / 9) ? 1 : 2;
}
__device__ __forceinline__ Seg get_seg(int cl, int rank, int w, int sg) {
  Seg s;
  if (cl < 63) {
    const int f = cl / 9, c = cl - f * 9;
    s.f = f;
    if (rank == 0) { s.qrow = 128 * c + 64 * w; s.blk0 = 0; s.nblk = 5; s.kind = K_EXCH; s.slot = 0; }
    else if (sg == 0) { s.qrow = 1152 + 64 * w; s.blk0 = c; s.nblk = 1; s.kind = K_PART_L; s.slot = f * 9 + c; }
    else { s.qrow = 128 * c + 64 * w; s.blk0 = 5; s.nblk = 4; s.kind = K_EXCH; s.slot = 0; }
  } else {
    const int u = ((cl - 63) * 2 + rank) * 2 + w;
    const int lo = u_lo(u), hi = u_lo(u + 1);
    const int f0 = lo / 9;
    const int mid = min(hi, 9 * (f0 + 1));
    s.qrow = 1280; s.kind = K_PART_U; s.slot = u * 2 + sg;
    if (sg == 0) { s.f = f0; s.blk0 = lo - 9 * f0; s.nblk = mid - lo; }
    else { s.f = f0 + 1; s.blk0 = 0; s.nblk = hi - mid; }
  }
  return s;
}

__device__ __forceinline__ void wait_counter(const unsigned int* p, unsigned int target) {
  for (uint32_t it = 0; it < SPIN_LIMIT; ++it) {
    unsigned int v;
    asm volatile("ld.acquire.gpu.global.u32 %0, [%1];" : "=r"(v) : "l"(p) : "memory");
    if (v >= target) return;
    __nanosleep(64);
  }
  __trap();
}

__device__ __forceinline__ void store_out(const float (&acc)[96], const uint32_t (&xr)[48], __nv_bfloat16* __restrict__ out,
                                          size_t grow, int r0, int nvalid, int q) {
  uint32_t* o0 = reinterpret_cast<uint32_t*>(out + (grow + r0) * C_) + q;
  uint32_t* o1 = o0 + 8 * (C_ / 2);
  const bool v0 = r0 < nvalid, v1 = r0 + 8 < nvalid;
#pragma unroll
  for (int j = 0; j < 24; ++j) {
    if (v0) o0[4 * j] = pack_bf16(bf_lo(xr[2 * j]) + acc[4 * j], bf_hi(xr[2 * j]) + acc[4 * j + 1]);
    if (v1) o1[4 * j] = pack_bf16(bf_lo(xr[2 * j + 1]) + acc[4 * j + 2], bf_hi(xr[2 * j + 1]) + acc[4 * j + 3]);
  }
}
__device__ __forceinline__ void load_x1(uint32_t (&xr)[48], size_t grow, int r0, int nvalid, int q) {
  const uint32_t* p0 = reinterpret_cast<const uint32_t*>(g_x1 + (grow + r0) * C_) + q;
  const uint32_t* p1 = p0 + 8 * (C_ / 2);
  const bool v0 = r0 < nvalid, v1 = r0 + 8 < nvalid;
#pragma unroll
  for (int j = 0; j < 24; ++j) {
    xr[2 * j] = v0 ? __ldcg(p0 + 4 * j) : 0u;
    xr[2 * j + 1] = v1 ? __ldcg(p1 + 4 * j) : 0u;
  }
}

template <int NR>
__device__ __forceinline__ void combine_rows(uint8_t* tile, int t, int np, const float* const* po, const float* const* pm, const float* const* pl) {
  constexpr int TPR = 128 / NR;
  constexpr int CPT = 192 / TPR;
  const int row = t / TPR, c0 = (t % TPR) * CPT;
  float mx = -INFINITY;
  for (int i = 0; i < np; ++i) mx = fmaxf(mx, __ldcg(pm[i] + row));
  float l = 0.f;
  float o[CPT];
#pragma unroll
  for (int c = 0; c < CPT; ++c) o[c] = 0.f;
  for (int i = 0; i < np; ++i) {
    const float wgt = ex2((__ldcg(pm[i] + row) - mx) * SM_SCALE_LOG2);
    l += wgt * __ldcg(pl[i] + row);
    const float4* src = reinterpret_cast<const float4*>(po[i] + row * 192 + c0);
#pragma unroll
    for (int c = 0; c < CPT / 4; ++c) {
      const float4 v = __ldcg(src + c);
      o[4 * c] += wgt * v.x; o[4 * c + 1] += wgt * v.y; o[4 * c + 2] += wgt * v.z; o[4 * c + 3] += wgt * v.w;
    }
  }
  const float inv = 1.f / l;
#pragma unroll
  for (int c = 0; c < CPT / 4; ++c) {
    const int col = c0 + 4 * c;
    uint2 v = make_uint2(pack_bf16(o[4 * c] * inv, o[4 * c + 1] * inv), pack_bf16(o[4 * c + 2] * inv, o[4 * c + 3] * inv));
    *reinterpret_cast<uint2*>(tile + (col >> 6) * 8192 + swz(row, col & 63) * 2) = v;
  }
}

__global__ void __cluster_dims__(2, 1, 1) __launch_bounds__(384, 1) p2_kernel(__nv_bfloat16* __restrict__ out) {
  extern __shared__ uint8_t smem_raw[];
  const uint32_t sbase = (smem_u32(smem_raw) + 1023) & ~1023u;
  uint8_t* sptr = smem_raw + (sbase - smem_u32(smem_raw));
  const uint32_t sQ = sbase + P2_Q_OFF, sML = sbase + P2_ML_OFF, bars = sbase + P2_BAR_OFF;
  const uint32_t bFull = bars, bEmpty = bars + 24, bQFull = bars + 48, bQEmpty = bars + 64, bW = bars + 80, bXFree = bars + 88, bXFull = bars + 96;
  const int tid = threadIdx.x, warp = tid >> 5, lane = tid & 31;
  const int cl = blockIdx.x >> 1, rank = blockIdx.x & 1;
  const bool modeB = cl >= 63;
  if (tid == 0) {
    for (int i = 0; i < NSTAGE; ++i) { mbar_init(bFull + 8 * i, 1); mbar_init(bEmpty + 8 * i, modeB ? 4 : 8); }
    for (int i = 0; i < 2; ++i) { mbar_init(bQFull + 8 * i, 1); mbar_init(bQEmpty + 8 * i, 4); }
    mbar_init(bW, 1); mbar_init(bXFree, 8); mbar_init(bXFull, 128);
    fence_mbar_init();
  }
  cluster_sync_all();
  pdl_wait();

  int nb0 = 0, nb1 = 0;
  {
    const int ns0 = num_segs(cl, rank, 0), ns1 = num_segs(cl, rank, 1);
    for (int sg = 0; sg < ns0; ++sg) nb0 += get_seg(cl, rank, 0, sg).nblk;
    for (int sg = 0; sg < ns1; ++sg) nb1 += get_seg(cl, rank, 1, sg).nblk;
  }
  const int firstW = (modeB && nb1 > nb0) ? 1 : 0;
  const int ntot = modeB ? nb0 + nb1 : nb0;
  const uint32_t sW0 = sbase + (ntot % NSTAGE) * STAGE_BYTES, sW1 = sW0 + WCH, sW2 = sbase + ((ntot + 1) % NSTAGE) * STAGE_BYTES;

  if (warp >= 8) {
    asm volatile("setmaxnreg.dec.sync.aligned.u32 40;");
    if (warp == 8 && lane == 0) {
      for (int i = 0; i < ntot; ++i) {
        const int w = modeB ? ((firstW + i) & 1) : 0;
        int k = modeB ? (i >> 1) : i;
        Seg s = get_seg(cl, rank, w, 0);
        if (k >= s.nblk) { k -= s.nblk; s = get_seg(cl, rank, w, 1); }
        const int st = i % NSTAGE;
        if (i >= NSTAGE) mbar_wait(bEmpty + 8 * st, ((i / NSTAGE) - 1) & 1);
        mbar_expect_tx(bFull + 8 * st, STAGE_BYTES);
        const __nv_bfloat16* src = g_h2 + (size_t)(s.f * 3) * (N_ * 64) + (size_t)(s.blk0 + k) * KB * 64;
#pragma unroll
        for (int ch = 0; ch < 3; ++ch) bulk_g2s(sbase + st * STAGE_BYTES + ch * KCH, src + (size_t)ch * (N_ * 64), KCH, bFull + 8 * st);
      }
      const __nv_bfloat16* wsrc = g_w + 3 * 3 * 192 * 64;
      mbar_expect_tx(bW, W_BYTES);
      mbar_wait(bEmpty + 8 * (ntot % NSTAGE), ((ntot / NSTAGE) - 1) & 1);
      bulk_g2s(sW0, wsrc, 2 * WCH, bW);
      mbar_wait(bEmpty + 8 * ((ntot + 1) % NSTAGE), (((ntot + 1) / NSTAGE) - 1) & 1);
      bulk_g2s(sW2, wsrc + 2 * 192 * 64, WCH, bW);
    } else if (warp == 9 && lane == 0) {
      for (int sg = 0; sg < 2; ++sg) {
        for (int w = 0; w < 2; ++w) {
          if (sg >= num_segs(cl, rank, w)) continue;
          const Seg s = get_seg(cl, rank, w, sg);
          if (sg > 0) mbar_wait(bQEmpty + 8 * w, 0);
          mbar_expect_tx(bQFull + 8 * w, TILE_BYTES);
          const __nv_bfloat16* src = g_q2 + (size_t)(s.f * 3) * (N_ * 64) + (size_t)s.qrow * 64;
#pragma unroll
          for (int ch = 0; ch < 3; ++ch) bulk_g2s(sQ + w * TILE_BYTES + ch * 8192, src + (size_t)ch * (N_ * 64), 8192, bQFull + 8 * w);
        }
      }
    }
    return;
  }

  asm volatile("setmaxnreg.inc.sync.aligned.u32 232;");
  const int w = warp >> 2, wl = warp & 3, t = tid & 127;
  const int g = lane >> 2, q = lane & 3;
  const int r0 = wl * 16 + g;
  const uint32_t sQt = sQ + w * TILE_BYTES;
  const int nseg = num_segs(cl, rank, w);
  float o[96];
  float m0, m1, l0, l1;
  int k = 0;
  Seg s;
  for (int sg = 0; sg < nseg; ++sg) {
    s = get_seg(cl, rank, w, sg);
    mbar_wait(bQFull + 8 * w, sg & 1);
    m0 = m1 = -INFINITY; l0 = l1 = 0.f;
    for (int b = 0; b < s.nblk; ++b, ++k) {
      const int i = modeB ? (2 * k + ((w - firstW) & 1)) : k;
      const int st = i % NSTAGE;
      const uint32_t sK = sbase + st * STAGE_BYTES;
      mbar_wait(bFull + 8 * st, (i / NSTAGE) & 1);
      float sc[72];
      wg_fence();
#pragma unroll
      for (int kk = 0; kk < 12; ++kk)
        wgmma_ss_n144<0>(sc, make_desc(sQt + (kk >> 2) * 8192 + (kk & 3) * 32, 16, 1024),
                         make_desc(sK + (kk >> 2) * KCH + (kk & 3) * 32, 16, 1024), kk > 0);
      wg_commit();
      wg_wait<0>();
      fence_regs(sc);
      if (b == s.nblk - 1 && lane == 0) {
        if (sg + 1 < nseg) mbar_arrive(bQEmpty + 8 * w);
        else if (s.kind == K_EXCH) mbar_arrive_remote(mapa(bXFree, rank ^ 1));
      }
      float mx0 = sc[0], mx1 = sc[2];
#pragma unroll
      for (int j = 0; j < 18; ++j) {
        mx0 = fmaxf(mx0, fmaxf(sc[4 * j], sc[4 * j + 1]));
        mx1 = fmaxf(mx1, fmaxf(sc[4 * j + 2], sc[4 * j + 3]));
      }
      mx0 = fmaxf(mx0, __shfl_xor_sync(0xffffffffu, mx0, 1)); mx0 = fmaxf(mx0, __shfl_xor_sync(0xffffffffu, mx0, 2));
      mx1 = fmaxf(mx1, __shfl_xor_sync(0xffffffffu, mx1, 1)); mx1 = fmaxf(mx1, __shfl_xor_sync(0xffffffffu, mx1, 2));
      const float mn0 = fmaxf(m0, mx0), mn1 = fmaxf(m1, mx1);
      const float a0 = ex2((m0 - mn0) * SM_SCALE_LOG2), a1 = ex2((m1 - mn1) * SM_SCALE_LOG2);
      m0 = mn0; m1 = mn1;
      const float ms0 = mn0 * SM_SCALE_LOG2, ms1 = mn1 * SM_SCALE_LOG2;
      float ls0 = 0.f, ls1 = 0.f;
      uint32_t pf[36];
#pragma unroll
      for (int j = 0; j < 18; ++j) {
        const float p0 = ex2(fmaf(sc[4 * j], SM_SCALE_LOG2, -ms0)), p1 = ex2(fmaf(sc[4 * j + 1], SM_SCALE_LOG2, -ms0));
        const float p2 = ex2(fmaf(sc[4 * j + 2], SM_SCALE_LOG2, -ms1)), p3 = ex2(fmaf(sc[4 * j + 3], SM_SCALE_LOG2, -ms1));
        ls0 += p0 + p1; ls1 += p2 + p3;
        pf[2 * j] = pack_bf16(p0, p1);
        pf[2 * j + 1] = pack_bf16(p2, p3);
      }
      l0 = l0 * a0 + ls0; l1 = l1 * a1 + ls1;
      if (b > 0) {
#pragma unroll
        for (int j = 0; j < 24; ++j) { o[4 * j] *= a0; o[4 * j + 1] *= a0; o[4 * j + 2] *= a1; o[4 * j + 3] *= a1; }
      }
      wg_fence();
#pragma unroll
      for (int kk = 0; kk < 9; ++kk)
        wgmma_rs_n192<1>(o, pf[4 * kk], pf[4 * kk + 1], pf[4 * kk + 2], pf[4 * kk + 3], make_desc(sK + kk * 2048, KCH, 1024), (b > 0) || (kk > 0));
      wg_commit();
      wg_wait<0>();
      fence_regs(o);
      if (lane == 0) mbar_arrive(bEmpty + 8 * st);
    }
    l0 += __shfl_xor_sync(0xffffffffu, l0, 1); l0 += __shfl_xor_sync(0xffffffffu, l0, 2);
    l1 += __shfl_xor_sync(0xffffffffu, l1, 1); l1 += __shfl_xor_sync(0xffffffffu, l1, 2);
    if (s.kind != K_EXCH) {
      float* po; float* pm; float* pl; unsigned int* cnt;
      bool valid;
      if (s.kind == K_PART_L) {
        po = g_pL + ((size_t)s.slot * 128 + 64 * w) * 192; pm = g_mL + s.slot * 128 + 64 * w; pl = g_lL + s.slot * 128 + 64 * w;
        cnt = g_cnt + s.f; valid = true;
      } else {
        po = g_pU + (size_t)s.slot * 16 * 192; pm = g_mU + s.slot * 16; pl = g_lU + s.slot * 16;
        cnt = g_cnt + 8 + s.f; valid = (wl == 0);
      }
      if (valid) {
        float2* d0 = reinterpret_cast<float2*>(po + r0 * 192) + q;
        float2* d1 = d0 + 8 * 96;
#pragma unroll
        for (int j = 0; j < 24; ++j) {
          d0[4 * j] = make_float2(o[4 * j], o[4 * j + 1]);
          d1[4 * j] = make_float2(o[4 * j + 2], o[4 * j + 3]);
        }
        if (q == 0) { pm[r0] = m0; pm[r0 + 8] = m1; pl[r0] = l0; pl[r0 + 8] = l1; }
      }
      __threadfence();
      named_bar(1 + w, 128);
      if (t == 0) atomicAdd(cnt, 1u);
    }
  }

  uint32_t xr[48];
  if (!modeB) {
    const int c = cl - s.f * 9;
    if (w != rank) {
      mbar_wait_cluster(bXFree, 0);
      const uint32_t rq = mapa(sQ, rank ^ 1) + t * 16;
#pragma unroll
      for (int i = 0; i < 24; ++i) st_cluster_v4(rq + i * 2048, o[4 * i], o[4 * i + 1], o[4 * i + 2], o[4 * i + 3]);
      st_cluster_v4(mapa(sML, rank ^ 1) + t * 16, m0, m1, l0, l1);
      mbar_arrive_remote(mapa(bXFull, rank ^ 1));
      if (c < 8) {
        const int lr = (2 * c + rank) * 8;
        if (t == 0) wait_counter(g_cnt + s.f, 18);
        named_bar(1 + w, 128);
        __threadfence();
        const float* po[9]; const float* pm[9]; const float* pl[9];
#pragma unroll
        for (int i = 0; i < 9; ++i) {
          po[i] = g_pL + ((size_t)(s.f * 9 + i) * 128 + lr) * 192; pm[i] = g_mL + (s.f * 9 + i) * 128 + lr; pl[i] = g_lL + (s.f * 9 + i) * 128 + lr;
        }
        mbar_wait(bW, 0);
        uint8_t* tile = sptr + (sW2 - sbase) + WCH;
        combine_rows<8>(tile, t, 9, po, pm, pl);
        fence_async_smem();
        named_bar(1 + w, 128);
        gemm_ss_w(o, sW2 + WCH, sW0, sW1, sW2);
        const size_t grow = (size_t)s.f * N_ + 1152 + lr;
        load_x1(xr, grow, r0, 8, q);
        wg_wait<0>();
        fence_regs(o);
        store_out(o, xr, out, grow, r0, 8, q);
      }
    } else {
      const size_t grow = (size_t)s.f * N_ + s.qrow;
      load_x1(xr, grow, r0, 64, q);
      mbar_wait_cluster(bXFull, 0);
      const float4 ml = *reinterpret_cast<const float4*>(sptr + P2_ML_OFF + t * 16);
      const float mn0 = fmaxf(m0, ml.x), mn1 = fmaxf(m1, ml.y);
      float a0 = ex2((m0 - mn0) * SM_SCALE_LOG2), a1 = ex2((m1 - mn1) * SM_SCALE_LOG2);
      float b0 = ex2((ml.x - mn0) * SM_SCALE_LOG2), b1 = ex2((ml.y - mn1) * SM_SCALE_LOG2);
      const float i0 = 1.f / (a0 * l0 + b0 * ml.z), i1 = 1.f / (a1 * l1 + b1 * ml.w);
      a0 *= i0; b0 *= i0; a1 *= i1; b1 *= i1;
      uint32_t af[48];
#pragma unroll
      for (int i = 0; i < 24; ++i) {
        const float4 v = *reinterpret_cast<const float4*>(sptr + P2_Q_OFF + i * 2048 + t * 16);
        af[2 * i] = pack_bf16(a0 * o[4 * i] + b0 * v.x, a0 * o[4 * i + 1] + b0 * v.y);
        af[2 * i + 1] = pack_bf16(a1 * o[4 * i + 2] + b1 * v.z, a1 * o[4 * i + 3] + b1 * v.w);
      }
      mbar_wait(bW, 0);
      gemm_rs_w(o, af, sW0, sW1, sW2);
      wg_wait<0>();
      fence_regs(o);
      store_out(o, xr, out, grow, r0, 64, q);
    }
  } else {
    const int u = ((cl - 63) * 2 + rank) * 2 + w;
    const int f = s.f;
    const bool fin = (u == 0) ? true : ((u_lo(u) - 1) / 9 != f);
    if (fin) {
      const float* po[3]; const float* pm[3]; const float* pl[3];
      int np = 0;
      for (int uu = 0; uu < 12; ++uu) {
        const int lo = u_lo(uu), hi = u_lo(uu + 1);
        if (hi <= 9 * f || lo >= 9 * f + 9) continue;
        const int slot = uu * 2 + ((lo / 9 == f) ? 0 : 1);
        const float* a = g_pU + (size_t)slot * 16 * 192; const float* b = g_mU + slot * 16; const float* c = g_lU + slot * 16;
        if (np == 0) { po[0] = a; pm[0] = b; pl[0] = c; } else if (np == 1) { po[1] = a; pm[1] = b; pl[1] = c; } else { po[2] = a; pm[2] = b; pl[2] = c; }
        ++np;
      }
      if (t == 0) wait_counter(g_cnt + 8 + f, np);
      named_bar(1 + w, 128);
      __threadfence();
      uint8_t* tile = sptr + P2_Q_OFF + w * TILE_BYTES;
      combine_rows<16>(tile, t, np, po, pm, pl);
      fence_async_smem();
      named_bar(1 + w, 128);
      mbar_wait(bW, 0);
      gemm_ss_w(o, sQt, sW0, sW1, sW2);
      const size_t grow = (size_t)f * N_ + 1280;
      load_x1(xr, grow, r0, 16, q);
      wg_wait<0>();
      fence_regs(o);
      store_out(o, xr, out, grow, r0, 16, q);
    }
  }
}

}

extern "C" void kernel_launch(void* const* d_in, const int* in_sizes, int n_in, void* d_out, int out_size) {
  using namespace tsf;
  const __nv_bfloat16* x = (const __nv_bfloat16*)d_in[0];
  const __nv_bfloat16* wqkv_t = (const __nv_bfloat16*)d_in[1];
  const __nv_bfloat16* wo_t = (const __nv_bfloat16*)d_in[2];
  const __nv_bfloat16* wqkv_s = (const __nv_bfloat16*)d_in[3];
  const __nv_bfloat16* wo_s = (const __nv_bfloat16*)d_in[4];
  __nv_bfloat16* out = (__nv_bfloat16*)d_out;
  static bool init = false;
  if (!init) {
    cudaFuncSetAttribute(p1_kernel, cudaFuncAttributeMaxDynamicSharedMemorySize, P1_SMEM);
    cudaFuncSetAttribute(p2_kernel, cudaFuncAttributeMaxDynamicSharedMemorySize, P2_SMEM);
    init = true;
  }
  cudaStream_t st = cudaStreamPerThread;
  p0_kernel<<<144, 128, 0, st>>>(wqkv_t, wo_t, wqkv_s, wo_s);
  cudaLaunchAttribute at[1];
  at[0].id = cudaLaunchAttributeProgrammaticStreamSerialization;
  at[0].val.programmaticStreamSerializationAllowed = 1;
  {
    cudaLaunchConfig_t cfg = {};
    cfg.gridDim = dim3(72); cfg.blockDim = dim3(384); cfg.dynamicSmemBytes = P1_SMEM; cfg.stream = st;
    cfg.attrs = at; cfg.numAttrs = 1;
    cudaLaunchKernelEx(&cfg, p1_kernel, x);
  }
  {
    cudaLaunchConfig_t cfg = {};
    cfg.gridDim = dim3(132); cfg.blockDim = dim3(384); cfg.dynamicSmemBytes = P2_SMEM; cfg.stream = st;
    cfg.attrs = at; cfg.numAttrs = 1;
    cudaLaunchKernelEx(&cfg, p2_kernel, out);
  }
}
```

```cpp
#include <cuda_runtime.h>
#include <cuda_bf16.h>
#include <stdint.h>

namespace tsf {

constexpr int T_ = 7, N_ = 1296, C_ = 192, ROWS = T_ * N_;
constexpr float SM_SCALE_LOG2 = 0.07216878364870322f * 1.4426950408889634f;
constexpr uint32_t SPIN_LIMIT = 1u << 24;

__device__ __align__(1024) __nv_bfloat16 g_w[4 * 3 * 192 * 64];
__device__ __align__(1024) __nv_bfloat16 g_x1[ROWS * C_];
__device__ __align__(1024) __nv_bfloat16 g_h2[T_ * 3 * N_ * 64];
__device__ __align__(1024) __nv_bfloat16 g_q2[T_ * 3 * N_ * 64 + 64 * 64];
__device__ __align__(1024) float g_part[(126 + 24) * 64 * 192];
__device__ float2 g_pml[(126 + 24) * 64];
__device__ unsigned int g_cnt[24];

#define PROF(kern, slot, idx)
__device__ __forceinline__ uint32_t smem_u32(const void* p) { return (uint32_t)__cvta_generic_to_shared(p); }
__device__ __forceinline__ void mbar_init(uint32_t bar, uint32_t count) {
  asm volatile("mbarrier.init.shared::cta.b64 [%0], %1;" ::"r"(bar), "r"(count) : "memory");
}
__device__ __forceinline__ void mbar_expect_tx(uint32_t bar, uint32_t bytes) {
  asm volatile("mbarrier.arrive.expect_tx.shared::cta.b64 _, [%0], %1;" ::"r"(bar), "r"(bytes) : "memory");
}
__device__ __forceinline__ void mbar_arrive(uint32_t bar) {
  asm volatile("mbarrier.arrive.shared::cta.b64 _, [%0];" ::"r"(bar) : "memory");
}
__device__ __forceinline__ void mbar_arrive_remote(uint32_t rbar) {
  asm volatile("mbarrier.arrive.release.cluster.shared::cluster.b64 _, [%0];" ::"r"(rbar) : "memory");
}
__device__ __forceinline__ bool mbar_try(uint32_t bar, uint32_t parity) {
  uint32_t ok;
  asm volatile("{\n.reg .pred p;\nmbarrier.try_wait.parity.shared::cta.b64 p, [%1], %2;\nselp.u32 %0, 1, 0, p;\n}\n"
               : "=r"(ok) : "r"(bar), "r"(parity) : "memory");
  return ok != 0;
}
__device__ __forceinline__ bool mbar_try_cluster(uint32_t bar, uint32_t parity) {
  uint32_t ok;
  asm volatile("{\n.reg .pred p;\nmbarrier.try_wait.parity.acquire.cluster.shared::cta.b64 p, [%1], %2;\nselp.u32 %0, 1, 0, p;\n}\n"
               : "=r"(ok) : "r"(bar), "r"(parity) : "memory");
  return ok != 0;
}
__device__ __forceinline__ void mbar_wait(uint32_t bar, uint32_t parity) {
#pragma unroll 1
  for (uint32_t it = 0; it < SPIN_LIMIT; ++it)
    if (mbar_try(bar, parity)) return;
  __trap();
}
__device__ __forceinline__ void mbar_wait_cluster(uint32_t bar, uint32_t parity) {
#pragma unroll 1
  for (uint32_t it = 0; it < SPIN_LIMIT; ++it)
    if (mbar_try_cluster(bar, parity)) return;
  __trap();
}
__device__ __forceinline__ void bulk_g2s(uint32_t dst, const void* src, uint32_t bytes, uint32_t bar) {
  asm volatile("cp.async.bulk.shared::cluster.global.mbarrier::complete_tx::bytes [%0], [%1], %2, [%3];"
               ::"r"(dst), "l"(src), "r"(bytes), "r"(bar) : "memory");
}
__device__ __forceinline__ void fence_async_smem() { asm volatile("fence.proxy.async.shared::cta;" ::: "memory"); }
__device__ __forceinline__ void fence_mbar_init() { asm volatile("fence.mbarrier_init.release.cluster;" ::: "memory"); }
__device__ __forceinline__ void named_bar(int id, int n) { asm volatile("bar.sync %0, %1;" ::"r"(id), "r"(n) : "memory"); }
__device__ __forceinline__ void wg_fence() { asm volatile("wgmma.fence.sync.aligned;" ::: "memory"); }
__device__ __forceinline__ void wg_commit() { asm volatile("wgmma.commit_group.sync.aligned;" ::: "memory"); }
template <int N> __device__ __forceinline__ void wg_wait() { asm volatile("wgmma.wait_group.sync.aligned %0;" ::"n"(N) : "memory"); }
template <int N> __device__ __forceinline__ void fence_regs(float (&d)[N]) {
#pragma unroll
  for (int i = 0; i < N; ++i) asm volatile("" : "+f"(d[i])::"memory");
}
__device__ __forceinline__ void pdl_wait() { asm volatile("griddepcontrol.wait;" ::: "memory"); }
__device__ __forceinline__ void pdl_launch() { asm volatile("griddepcontrol.launch_dependents;" ::: "memory"); }
__device__ __forceinline__ uint32_t mapa(uint32_t addr, uint32_t rank) {
  uint32_t r;
  asm volatile("mapa.shared::cluster.u32 %0, %1, %2;" : "=r"(r) : "r"(addr), "r"(rank));
  return r;
}
__device__ __forceinline__ void cluster_sync_all() {
  asm volatile("barrier.cluster.arrive.release.aligned;\nbarrier.cluster.wait.acquire.aligned;" ::: "memory");
}
__device__ __forceinline__ void st_cluster_v4(uint32_t addr, float a, float b, float c, float d) {
  asm volatile("st.shared::cluster.v4.f32 [%0], {%1, %2, %3, %4};" ::"r"(addr), "f"(a), "f"(b), "f"(c), "f"(d) : "memory");
}
__device__ __forceinline__ void st_async_v4(uint32_t addr, float a, float b, float c, float d, uint32_t rbar) {
  asm volatile("st.async.weak.shared::cluster.mbarrier::complete_tx::bytes.v4.f32 [%0], {%1, %2, %3, %4}, [%5];"
               ::"r"(addr), "f"(a), "f"(b), "f"(c), "f"(d), "r"(rbar) : "memory");
}
__device__ __forceinline__ uint64_t make_desc(uint32_t addr, uint32_t lbo, uint32_t sbo) {
  return (uint64_t)((addr & 0x3FFFF) >> 4) | ((uint64_t)(lbo >> 4) << 16) | ((uint64_t)(sbo >> 4) << 32) | (1ull << 62);
}
__device__ __forceinline__ uint32_t pack_bf16(float lo, float hi) {
  uint32_t r;
  asm("cvt.rn.bf16x2.f32 %0, %1, %2;" : "=r"(r) : "f"(hi), "f"(lo));
  return r;
}
__device__ __forceinline__ float bf_lo(uint32_t v) { return __uint_as_float(v << 16); }
__device__ __forceinline__ float bf_hi(uint32_t v) { return __uint_as_float(v & 0xffff0000u); }
__device__ __forceinline__ float ex2(float x) {
  float r;
  asm("ex2.approx.ftz.f32 %0, %1;" : "=f"(r) : "f"(x));
  return r;
}
__device__ __forceinline__ void stsm_x4(uint32_t addr, uint32_t r0, uint32_t r1, uint32_t r2, uint32_t r3) {
  asm volatile("stmatrix.sync.aligned.m8n8.x4.shared.b16 [%0], {%1, %2, %3, %4};" ::"r"(addr), "r"(r0), "r"(r1), "r"(r2), "r"(r3) : "memory");
}
__device__ __forceinline__ void bulk_s2g(void* dst, uint32_t src, uint32_t bytes) {
  asm volatile("cp.async.bulk.global.shared::cta.bulk_group [%0], [%1], %2;" ::"l"(dst), "r"(src), "r"(bytes) : "memory");
}
__device__ __forceinline__ void bulk_commit() { asm volatile("cp.async.bulk.commit_group;" ::: "memory"); }
__device__ __forceinline__ void bulk_wait_read() { asm volatile("cp.async.bulk.wait_group.read 0;" ::: "memory"); }
__device__ __forceinline__ void bulk_wait_all() { asm volatile("cp.async.bulk.wait_group 0;" ::: "memory"); }
__device__ __forceinline__ void named_arrive(int id, int n) { asm volatile("bar.arrive %0, %1;" ::"r"(id), "r"(n) : "memory"); }
__device__ __forceinline__ void wait_counter(const unsigned int* p, unsigned int target) {
#pragma unroll 1
  for (uint32_t it = 0; it < SPIN_LIMIT; ++it) {
    unsigned int v;
    asm volatile("ld.acquire.gpu.global.u32 %0, [%1];" : "=r"(v) : "l"(p) : "memory");
    if (v >= target) return;
    __nanosleep(32);
  }
  __trap();
}
__device__ __forceinline__ void fence_async_all() { asm volatile("fence.proxy.async;" ::: "memory"); }
__device__ __forceinline__ int swz(int row, int col) { return row * 64 + ((((col >> 3) ^ row) & 7) << 3) + (col & 7); }

template <int TA, int TB>
__device__ __forceinline__ void wgmma_ss_n48(float (&d)[24], uint64_t da, uint64_t db, int sc) {
  asm volatile("{\n.reg .pred p;\nsetp.ne.b32 p, %26, 0;\n"
    "wgmma.mma_async.sync.aligned.m64n48k16.f32.bf16.bf16 "
    "{%0, %1, %2, %3, %4, %5, %6, %7, %8, %9, %10, %11, %12, %13, %14, %15, %16, %17, %18, %19, %20, %21, %22, %23}, "
    "%24, %25, p, 1, 1, %27, %28;\n}\n"
    : "+f"(d[0]), "+f"(d[1]), "+f"(d[2]), "+f"(d[3]), "+f"(d[4]), "+f"(d[5]), "+f"(d[6]), "+f"(d[7]), "+f"(d[8]), "+f"(d[9]), "+f"(d[10]), "+f"(d[11]), "+f"(d[12]), "+f"(d[13]), "+f"(d[14]), "+f"(d[15]), "+f"(d[16]), "+f"(d[17]), "+f"(d[18]), "+f"(d[19]), "+f"(d[20]), "+f"(d[21]), "+f"(d[22]), "+f"(d[23])
    : "l"(da), "l"(db), "r"(sc), "n"(TA), "n"(TB));
}
template <int TB>
__device__ __forceinline__ void wgmma_ss_n192(float (&d)[96], uint64_t da, uint64_t db, int sc) {
  asm volatile("{\n.reg .pred p;\nsetp.ne.b32 p, %98, 0;\n"
    "wgmma.mma_async.sync.aligned.m64n192k16.f32.bf16.bf16 "
    "{%0, %1, %2, %3, %4, %5, %6, %7, %8, %9, %10, %11, %12, %13, %14, %15, %16, %17, %18, %19, %20, %21, %22, %23, %24, %25, %26, %27, %28, %29, %30, %31, %32, %33, %34, %35, %36, %37, %38, %39, %40, %41, %42, %43, %44, %45, %46, %47, %48, %49, %50, %51, %52, %53, %54, %55, %56, %57, %58, %59, %60, %61, %62, %63, %64, %65, %66, %67, %68, %69, %70, %71, %72, %73, %74, %75, %76, %77, %78, %79, %80, %81, %82, %83, %84, %85, %86, %87, %88, %89, %90, %91, %92, %93, %94, %95}, "
    "%96, %97, p, 1, 1, 0, %99;\n}\n"
    : "+f"(d[0]), "+f"(d[1]), "+f"(d[2]), "+f"(d[3]), "+f"(d[4]), "+f"(d[5]), "+f"(d[6]), "+f"(d[7]), "+f"(d[8]), "+f"(d[9]), "+f"(d[10]), "+f"(d[11]), "+f"(d[12]), "+f"(d[13]), "+f"(d[14]), "+f"(d[15]), "+f"(d[16]), "+f"(d[17]), "+f"(d[18]), "+f"(d[19]), "+f"(d[20]), "+f"(d[21]), "+f"(d[22]), "+f"(d[23]), "+f"(d[24]), "+f"(d[25]), "+f"(d[26]), "+f"(d[27]), "+f"(d[28]), "+f"(d[29]), "+f"(d[30]), "+f"(d[31]), "+f"(d[32]), "+f"(d[33]), "+f"(d[34]), "+f"(d[35]), "+f"(d[36]), "+f"(d[37]), "+f"(d[38]), "+f"(d[39]), "+f"(d[40]), "+f"(d[41]), "+f"(d[42]), "+f"(d[43]), "+f"(d[44]), "+f"(d[45]), "+f"(d[46]), "+f"(d[47]), "+f"(d[48]), "+f"(d[49]), "+f"(d[50]), "+f"(d[51]), "+f"(d[52]), "+f"(d[53]), "+f"(d[54]), "+f"(d[55]), "+f"(d[56]), "+f"(d[57]), "+f"(d[58]), "+f"(d[59]), "+f"(d[60]), "+f"(d[61]), "+f"(d[62]), "+f"(d[63]), "+f"(d[64]), "+f"(d[65]), "+f"(d[66]), "+f"(d[67]), "+f"(d[68]), "+f"(d[69]), "+f"(d[70]), "+f"(d[71]), "+f"(d[72]), "+f"(d[73]), "+f"(d[74]), "+f"(d[75]), "+f"(d[76]), "+f"(d[77]), "+f"(d[78]), "+f"(d[79]), "+f"(d[80]), "+f"(d[81]), "+f"(d[82]), "+f"(d[83]), "+f"(d[84]), "+f"(d[85]), "+f"(d[86]), "+f"(d[87]), "+f"(d[88]), "+f"(d[89]), "+f"(d[90]), "+f"(d[91]), "+f"(d[92]), "+f"(d[93]), "+f"(d[94]), "+f"(d[95])
    : "l"(da), "l"(db), "r"(sc), "n"(TB));
}
template <int TB>
__device__ __forceinline__ void wgmma_rs_n192(float (&d)[96], uint32_t a0, uint32_t a1, uint32_t a2, uint32_t a3, uint64_t db, int sc) {
  asm volatile("{\n.reg .pred p;\nsetp.ne.b32 p, %101, 0;\n"
    "wgmma.mma_async.sync.aligned.m64n192k16.f32.bf16.bf16 "
    "{%0, %1, %2, %3, %4, %5, %6, %7, %8, %9, %10, %11, %12, %13, %14, %15, %16, %17, %18, %19, %20, %21, %22, %23, %24, %25, %26, %27, %28, %29, %30, %31, %32, %33, %34, %35, %36, %37, %38, %39, %40, %41, %42, %43, %44, %45, %46, %47, %48, %49, %50, %51, %52, %53, %54, %55, %56, %57, %58, %59, %60, %61, %62, %63, %64, %65, %66, %67, %68, %69, %70, %71, %72, %73, %74, %75, %76, %77, %78, %79, %80, %81, %82, %83, %84, %85, %86, %87, %88, %89, %90, %91, %92, %93, %94, %95}, "
    "{%96, %97, %98, %99}, %100, p, 1, 1, %102;\n}\n"
    : "+f"(d[0]), "+f"(d[1]), "+f"(d[2]), "+f"(d[3]), "+f"(d[4]), "+f"(d[5]), "+f"(d[6]), "+f"(d[7]), "+f"(d[8]), "+f"(d[9]), "+f"(d[10]), "+f"(d[11]), "+f"(d[12]), "+f"(d[13]), "+f"(d[14]), "+f"(d[15]), "+f"(d[16]), "+f"(d[17]), "+f"(d[18]), "+f"(d[19]), "+f"(d[20]), "+f"(d[21]), "+f"(d[22]), "+f"(d[23]), "+f"(d[24]), "+f"(d[25]), "+f"(d[26]), "+f"(d[27]), "+f"(d[28]), "+f"(d[29]), "+f"(d[30]), "+f"(d[31]), "+f"(d[32]), "+f"(d[33]), "+f"(d[34]), "+f"(d[35]), "+f"(d[36]), "+f"(d[37]), "+f"(d[38]), "+f"(d[39]), "+f"(d[40]), "+f"(d[41]), "+f"(d[42]), "+f"(d[43]), "+f"(d[44]), "+f"(d[45]), "+f"(d[46]), "+f"(d[47]), "+f"(d[48]), "+f"(d[49]), "+f"(d[50]), "+f"(d[51]), "+f"(d[52]), "+f"(d[53]), "+f"(d[54]), "+f"(d[55]), "+f"(d[56]), "+f"(d[57]), "+f"(d[58]), "+f"(d[59]), "+f"(d[60]), "+f"(d[61]), "+f"(d[62]), "+f"(d[63]), "+f"(d[64]), "+f"(d[65]), "+f"(d[66]), "+f"(d[67]), "+f"(d[68]), "+f"(d[69]), "+f"(d[70]), "+f"(d[71]), "+f"(d[72]), "+f"(d[73]), "+f"(d[74]), "+f"(d[75]), "+f"(d[76]), "+f"(d[77]), "+f"(d[78]), "+f"(d[79]), "+f"(d[80]), "+f"(d[81]), "+f"(d[82]), "+f"(d[83]), "+f"(d[84]), "+f"(d[85]), "+f"(d[86]), "+f"(d[87]), "+f"(d[88]), "+f"(d[89]), "+f"(d[90]), "+f"(d[91]), "+f"(d[92]), "+f"(d[93]), "+f"(d[94]), "+f"(d[95])
    : "r"(a0), "r"(a1), "r"(a2), "r"(a3), "l"(db), "r"(sc), "n"(TB));
}
template <int TB>
__device__ __forceinline__ void wgmma_rs_n64(float (&d)[32], uint32_t a0, uint32_t a1, uint32_t a2, uint32_t a3, uint64_t db, int sc) {
  asm volatile("{\n.reg .pred p;\nsetp.ne.b32 p, %37, 0;\n"
    "wgmma.mma_async.sync.aligned.m64n64k16.f32.bf16.bf16 "
    "{%0, %1, %2, %3, %4, %5, %6, %7, %8, %9, %10, %11, %12, %13, %14, %15, %16, %17, %18, %19, %20, %21, %22, %23, %24, %25, %26, %27, %28, %29, %30, %31}, "
    "{%32, %33, %34, %35}, %36, p, 1, 1, %38;\n}\n"
    : "+f"(d[0]), "+f"(d[1]), "+f"(d[2]), "+f"(d[3]), "+f"(d[4]), "+f"(d[5]), "+f"(d[6]), "+f"(d[7]), "+f"(d[8]), "+f"(d[9]), "+f"(d[10]), "+f"(d[11]), "+f"(d[12]), "+f"(d[13]), "+f"(d[14]), "+f"(d[15]), "+f"(d[16]), "+f"(d[17]), "+f"(d[18]), "+f"(d[19]), "+f"(d[20]), "+f"(d[21]), "+f"(d[22]), "+f"(d[23]), "+f"(d[24]), "+f"(d[25]), "+f"(d[26]), "+f"(d[27]), "+f"(d[28]), "+f"(d[29]), "+f"(d[30]), "+f"(d[31])
    : "r"(a0), "r"(a1), "r"(a2), "r"(a3), "l"(db), "r"(sc), "n"(TB));
}
template <int TB>
__device__ __forceinline__ void wgmma_ss_n144(float (&d)[72], uint64_t da, uint64_t db, int sc) {
  asm volatile("{\n.reg .pred p;\nsetp.ne.b32 p, %74, 0;\n"
    "wgmma.mma_async.sync.aligned.m64n144k16.f32.bf16.bf16 "
    "{%0, %1, %2, %3, %4, %5, %6, %7, %8, %9, %10, %11, %12, %13, %14, %15, %16, %17, %18, %19, %20, %21, %22, %23, %24, %25, %26, %27, %28, %29, %30, %31, %32, %33, %34, %35, %36, %37, %38, %39, %40, %41, %42, %43, %44, %45, %46, %47, %48, %49, %50, %51, %52, %53, %54, %55, %56, %57, %58, %59, %60, %61, %62, %63, %64, %65, %66, %67, %68, %69, %70, %71}, "
    "%72, %73, p, 1, 1, 0, %75;\n}\n"
    : "+f"(d[0]), "+f"(d[1]), "+f"(d[2]), "+f"(d[3]), "+f"(d[4]), "+f"(d[5]), "+f"(d[6]), "+f"(d[7]), "+f"(d[8]), "+f"(d[9]), "+f"(d[10]), "+f"(d[11]), "+f"(d[12]), "+f"(d[13]), "+f"(d[14]), "+f"(d[15]), "+f"(d[16]), "+f"(d[17]), "+f"(d[18]), "+f"(d[19]), "+f"(d[20]), "+f"(d[21]), "+f"(d[22]), "+f"(d[23]), "+f"(d[24]), "+f"(d[25]), "+f"(d[26]), "+f"(d[27]), "+f"(d[28]), "+f"(d[29]), "+f"(d[30]), "+f"(d[31]), "+f"(d[32]), "+f"(d[33]), "+f"(d[34]), "+f"(d[35]), "+f"(d[36]), "+f"(d[37]), "+f"(d[38]), "+f"(d[39]), "+f"(d[40]), "+f"(d[41]), "+f"(d[42]), "+f"(d[43]), "+f"(d[44]), "+f"(d[45]), "+f"(d[46]), "+f"(d[47]), "+f"(d[48]), "+f"(d[49]), "+f"(d[50]), "+f"(d[51]), "+f"(d[52]), "+f"(d[53]), "+f"(d[54]), "+f"(d[55]), "+f"(d[56]), "+f"(d[57]), "+f"(d[58]), "+f"(d[59]), "+f"(d[60]), "+f"(d[61]), "+f"(d[62]), "+f"(d[63]), "+f"(d[64]), "+f"(d[65]), "+f"(d[66]), "+f"(d[67]), "+f"(d[68]), "+f"(d[69]), "+f"(d[70]), "+f"(d[71])
    : "l"(da), "l"(db), "r"(sc), "n"(TB));
}

__device__ __forceinline__ void fuse_weights(uint32_t sbase, uint8_t* sptr, int j, const __nv_bfloat16* __restrict__ wqkv_t,
                                             const __nv_bfloat16* __restrict__ wo_t, const __nv_bfloat16* __restrict__ wqkv_s,
                                             const __nv_bfloat16* __restrict__ wo_s) {
  const int m = j / 12, n0 = ((j % 12) >> 2) * 64, k0 = (j & 3) * 48;
  const __nv_bfloat16* wqkv = (m < 2) ? wqkv_t : wqkv_s;
  const __nv_bfloat16* wo = (m < 2) ? wo_t : wo_s;
  const int tid = threadIdx.x;
  const bool odd = m & 1;
  uint8_t* pA = sptr; uint8_t* pB = sptr + 24576;
  uint4 va[4], vb[3];
#pragma unroll
  for (int i = 0; i < 4; ++i) {
    const int u = tid + i * 384;
    const int row = odd ? (u >> 3) : (u / 24), cu = odd ? (u & 7) : (u % 24);
    va[i] = __ldg(reinterpret_cast<const uint4*>(odd ? (wo + row * 192 + n0 + cu * 8) : (wqkv + (n0 + row) * 576 + 192 + cu * 8)));
  }
#pragma unroll
  for (int i = 0; i < 3; ++i) {
    const int u = tid + i * 384, row = u / 24, cu = u % 24;
    vb[i] = __ldg(reinterpret_cast<const uint4*>(wqkv + (k0 + row) * 576 + (odd ? 384 : 0) + cu * 8));
  }
#pragma unroll
  for (int i = 0; i < 4; ++i) {
    const int u = tid + i * 384;
    const int row = odd ? (u >> 3) : (u / 24), cu = odd ? (u & 7) : (u % 24);
    *reinterpret_cast<uint4*>(pA + (cu >> 3) * 8192 + row * 128 + (((cu ^ row) & 7) << 4)) = va[i];
  }
#pragma unroll
  for (int i = 0; i < 3; ++i) {
    const int u = tid + i * 384, row = u / 24, cu = u % 24;
    *reinterpret_cast<uint4*>(pB + (cu >> 3) * 6144 + row * 128 + (((cu ^ row) & 7) << 4)) = vb[i];
  }
  fence_async_smem();
  __syncthreads();
  if (tid < 128) {
    float acc[24];
    const uint64_t dB = make_desc(sbase + 24576, 16, 1024);
    wg_fence();
    if (odd) {
      const uint64_t dA = make_desc(sbase, 8192, 1024);
#pragma unroll
      for (int kk = 0; kk < 12; ++kk) wgmma_ss_n48<1, 0>(acc, dA + kk * 128, dB + ((kk >> 2) * 384 + (kk & 3) * 2), kk > 0);
    } else {
      const uint64_t dA = make_desc(sbase, 16, 1024);
#pragma unroll
      for (int kk = 0; kk < 12; ++kk) wgmma_ss_n48<0, 0>(acc, dA + ((kk >> 2) * 512 + (kk & 3) * 2), dB + ((kk >> 2) * 384 + (kk & 3) * 2), kk > 0);
    }
    wg_commit();
    wg_wait<0>();
    fence_regs(acc);
    const int lane = tid & 31, r0 = n0 + (tid >> 5) * 16 + (lane >> 2);
    __nv_bfloat16* dst = g_w + (size_t)m * 3 * 192 * 64;
#pragma unroll
    for (int jj = 0; jj < 6; ++jj) {
      const int k = k0 + 8 * jj + 2 * (lane & 3);
      __nv_bfloat16* ch = dst + (k >> 6) * (192 * 64);
      *reinterpret_cast<uint32_t*>(ch + swz(r0, k & 63)) = pack_bf16(acc[4 * jj], acc[4 * jj + 1]);
      *reinterpret_cast<uint32_t*>(ch + swz(r0 + 8, k & 63)) = pack_bf16(acc[4 * jj + 2], acc[4 * jj + 3]);
    }
    __threadfence();
    named_bar(1, 128);
    if (tid == 0) atomicAdd(g_cnt + 16 + m, 1u);
  }
}

constexpr int W_BYTES = 3 * 192 * 128;
constexpr int WCH = 192 * 128;
constexpr int TILE_BYTES = 3 * 64 * 128;
constexpr int P1_SMEM = 2 * W_BYTES + 2 * TILE_BYTES + 128 + 1024;

__device__ __forceinline__ void gemm_rs_w(float (&acc)[96], const uint32_t (&a)[48], uint32_t c0, uint32_t c1, uint32_t c2) {
  wg_fence();
#pragma unroll
  for (int kk = 0; kk < 12; ++kk) {
    const uint32_t base = (kk < 4) ? c0 : ((kk < 8) ? c1 : c2);
    wgmma_rs_n192<0>(acc, a[4 * kk], a[4 * kk + 1], a[4 * kk + 2], a[4 * kk + 3], make_desc(base + (kk & 3) * 32, 16, 1024), kk > 0);
  }
  wg_commit();
}
__device__ __forceinline__ void gemm_ss_w(float (&acc)[96], uint32_t atile, uint32_t c0, uint32_t c1, uint32_t c2) {
  wg_fence();
#pragma unroll
  for (int kk = 0; kk < 12; ++kk) {
    const uint32_t base = (kk < 4) ? c0 : ((kk < 8) ? c1 : c2);
    wgmma_ss_n192<0>(acc, make_desc(atile + (kk >> 2) * 8192 + (kk & 3) * 32, 16, 1024), make_desc(base + (kk & 3) * 32, 16, 1024), kk > 0);
  }
  wg_commit();
}

__global__ void __launch_bounds__(384, 1) p1_kernel(const __nv_bfloat16* __restrict__ x, const __nv_bfloat16* __restrict__ wqkv_t,
                                                    const __nv_bfloat16* __restrict__ wo_t, const __nv_bfloat16* __restrict__ wqkv_s,
                                                    const __nv_bfloat16* __restrict__ wo_s) {
  extern __shared__ uint8_t smem_raw[];
  const uint32_t sbase = (smem_u32(smem_raw) + 1023) & ~1023u;
  uint8_t* sptr = smem_raw + (sbase - smem_u32(smem_raw));
  if (blockIdx.x >= 72) {
    PROF(0, 0, 0);
    pdl_launch();
    if (blockIdx.x == 131 && threadIdx.x < 16) g_cnt[threadIdx.x] = 0;
    if (blockIdx.x < 120) fuse_weights(sbase, sptr, blockIdx.x - 72, wqkv_t, wo_t, wqkv_s, wo_s);
    PROF(0, 0, 1);
    return;
  }
  const uint32_t sWA = sbase, sWB = sbase + W_BYTES, sH = sbase + 2 * W_BYTES;
  const uint32_t bars = sH + 2 * TILE_BYTES;
  const int tid = threadIdx.x, warp = tid >> 5, lane = tid & 31;
  if (tid == 0) PROF(1, 3, 0);
  pdl_launch();
  if (tid == 0) {
    mbar_init(bars, 1); mbar_init(bars + 8, 1); mbar_init(bars + 16, 1); mbar_init(bars + 24, 8); mbar_init(bars + 32, 4); mbar_init(bars + 40, 4);
    fence_mbar_init();
  }
  __syncthreads();

  if (warp >= 8) {
    asm volatile("setmaxnreg.dec.sync.aligned.u32 40;");
    if (warp == 8 && lane == 0) {
      wait_counter(g_cnt + 16, 12);
      fence_async_all();
      mbar_expect_tx(bars, W_BYTES);
      bulk_g2s(sWA, g_w, W_BYTES, bars);
      wait_counter(g_cnt + 17, 12);
      fence_async_all();
      mbar_expect_tx(bars + 8, W_BYTES);
      bulk_g2s(sWB, g_w + 3 * 192 * 64, W_BYTES, bars + 8);
      wait_counter(g_cnt + 18, 12);
      fence_async_all();
      mbar_wait(bars + 24, 0);
      mbar_expect_tx(bars + 16, W_BYTES);
      bulk_g2s(sWA, g_w + 2 * 3 * 192 * 64, W_BYTES, bars + 16);
    }
    return;
  }

  asm volatile("setmaxnreg.inc.sync.aligned.u32 232;");
  const int wg = warp >> 2, t = tid & 127, wl = warp & 3;
  const int n0 = (blockIdx.x * 2 + wg) * 9;
  const uint32_t sHt = sH + wg * TILE_BYTES;
  PROF(1, wg, 0);
  uint8_t* pHt = sptr + 2 * W_BYTES + wg * TILE_BYTES;
  {
    const int row = t >> 1, half = t & 1;
    uint4 v[12];
    if (row < 63) {
      const int j = row / 7, tt = row - j * 7;
      const uint4* src = reinterpret_cast<const uint4*>(x + ((size_t)tt * N_ + n0 + j) * C_ + half * 96);
#pragma unroll
      for (int i = 0; i < 12; ++i) v[i] = __ldg(src + i);
    } else {
#pragma unroll
      for (int i = 0; i < 12; ++i) v[i] = make_uint4(0, 0, 0, 0);
    }
    float s = 0.f;
#pragma unroll
    for (int i = 0; i < 12; ++i) {
      s += bf_lo(v[i].x) + bf_hi(v[i].x) + bf_lo(v[i].y) + bf_hi(v[i].y) + bf_lo(v[i].z) + bf_hi(v[i].z) + bf_lo(v[i].w) + bf_hi(v[i].w);
    }
    s += __shfl_xor_sync(0xffffffffu, s, 1);
    const float mean = s * (1.f / 192.f);
    float ss = 0.f;
#pragma unroll
    for (int i = 0; i < 12; ++i) {
      const uint32_t w4[4] = {v[i].x, v[i].y, v[i].z, v[i].w};
#pragma unroll
      for (int e = 0; e < 4; ++e) {
        float a = bf_lo(w4[e]) - mean, b = bf_hi(w4[e]) - mean;
        ss += a * a + b * b;
      }
    }
    ss += __shfl_xor_sync(0xffffffffu, ss, 1);
    const float rstd = 1.f / sqrtf(ss * (1.f / 192.f) + 1e-5f);
#pragma unroll
    for (int i = 0; i < 12; ++i) {
      const uint32_t w4[4] = {v[i].x, v[i].y, v[i].z, v[i].w};
      uint32_t o4[4];
#pragma unroll
      for (int e = 0; e < 4; ++e) o4[e] = pack_bf16((bf_lo(w4[e]) - mean) * rstd, (bf_hi(w4[e]) - mean) * rstd);
      const int col = half * 96 + i * 8;
      *reinterpret_cast<uint4*>(pHt + (col >> 6) * 8192 + row * 128 + ((((col >> 3) ^ row) & 7) << 4)) = make_uint4(o4[0], o4[1], o4[2], o4[3]);
    }
  }
  PROF(1, wg, 1);
  fence_async_smem();
  named_bar(1 + wg, 128);

  const int g = lane >> 2, q = lane & 3;
  const int r0 = wl * 16 + g, r1 = r0 + 8;
  float acc[96];
  uint32_t af[48];
  mbar_wait(bars, 0);
  PROF(1, wg, 2);
  gemm_ss_w(acc, sHt, sWA, sWA + WCH, sWA + 2 * WCH);
  wg_wait<0>();
  fence_regs(acc);
  PROF(1, wg, 3);
  if (lane == 0) mbar_arrive(bars + 24);
#pragma unroll
  for (int i = 0; i < 48; ++i) af[i] = pack_bf16(acc[2 * i], acc[2 * i + 1]);
  float sc[32];
  wg_fence();
#pragma unroll
  for (int kk = 0; kk < 12; ++kk)
    wgmma_rs_n64<0>(sc, af[4 * kk], af[4 * kk + 1], af[4 * kk + 2], af[4 * kk + 3],
                    make_desc(sHt + (kk >> 2) * 8192 + (kk & 3) * 32, 16, 1024), kk > 0);
  wg_commit();
  wg_wait<0>();
  fence_regs(sc);
  PROF(1, wg, 4);
  uint32_t pf[16];
  {
    const int g0 = r0 / 7, g1 = r1 / 7;
    float mx0 = -INFINITY, mx1 = -INFINITY;
#pragma unroll
    for (int j = 0; j < 8; ++j) {
#pragma unroll
      for (int e = 0; e < 2; ++e) {
        const int col = 8 * j + 2 * q + e;
        const int cg = col / 7;
        if (cg != g0) sc[4 * j + e] = -INFINITY;
        if (cg != g1) sc[4 * j + 2 + e] = -INFINITY;
        mx0 = fmaxf(mx0, sc[4 * j + e]);
        mx1 = fmaxf(mx1, sc[4 * j + 2 + e]);
      }
    }
    mx0 = fmaxf(mx0, __shfl_xor_sync(0xffffffffu, mx0, 1)); mx0 = fmaxf(mx0, __shfl_xor_sync(0xffffffffu, mx0, 2));
    mx1 = fmaxf(mx1, __shfl_xor_sync(0xffffffffu, mx1, 1)); mx1 = fmaxf(mx1, __shfl_xor_sync(0xffffffffu, mx1, 2));
    float l0 = 0.f, l1 = 0.f;
#pragma unroll
    for (int j = 0; j < 8; ++j) {
#pragma unroll
      for (int e = 0; e < 2; ++e) {
        sc[4 * j + e] = ex2((sc[4 * j + e] - mx0) * SM_SCALE_LOG2);
        sc[4 * j + 2 + e] = ex2((sc[4 * j + 2 + e] - mx1) * SM_SCALE_LOG2);
        l0 += sc[4 * j + e];
        l1 += sc[4 * j + 2 + e];
      }
    }
    l0 += __shfl_xor_sync(0xffffffffu, l0, 1); l0 += __shfl_xor_sync(0xffffffffu, l0, 2);
    l1 += __shfl_xor_sync(0xffffffffu, l1, 1); l1 += __shfl_xor_sync(0xffffffffu, l1, 2);
    const float i0 = 1.f / l0, i1 = 1.f / l1;
#pragma unroll
    for (int j = 0; j < 8; ++j) {
      pf[2 * j] = pack_bf16(sc[4 * j] * i0, sc[4 * j + 1] * i0);
      pf[2 * j + 1] = pack_bf16(sc[4 * j + 2] * i1, sc[4 * j + 3] * i1);
    }
  }
  wg_fence();
#pragma unroll
  for (int kk = 0; kk < 4; ++kk)
    wgmma_rs_n192<1>(acc, pf[4 * kk], pf[4 * kk + 1], pf[4 * kk + 2], pf[4 * kk + 3], make_desc(sHt + kk * 2048, 8192, 1024), kk > 0);
  wg_commit();
  wg_wait<0>();
  fence_regs(acc);
#pragma unroll
  for (int i = 0; i < 48; ++i) af[i] = pack_bf16(acc[2 * i], acc[2 * i + 1]);
  PROF(1, wg, 5);
  constexpr int FS = 3472;
  named_bar(1 + wg, 128);
  if (lane == 0) {
    mbar_expect_tx(bars + 32 + 8 * wg, (wl == 3 ? 1 : 2) * 3456);
#pragma unroll 1
    for (int tt = wl; tt < 7; tt += 4) bulk_g2s(sHt + tt * FS, x + ((size_t)tt * N_ + n0) * C_, 3456, bars + 32 + 8 * wg);
  }
  mbar_wait(bars + 8, 0);
  PROF(1, wg, 6);
  gemm_rs_w(acc, af, sWB, sWB + WCH, sWB + 2 * WCH);
  uint32_t xr[48];
  {
    const int j0 = r0 / 7, t0 = r0 - j0 * 7, j1 = min(r1, 62) / 7, t1 = min(r1, 62) - j1 * 7;
    const uint8_t* p0 = pHt + t0 * FS + j0 * 384 + q * 4;
    const uint8_t* p1 = pHt + t1 * FS + j1 * 384 + q * 4;
    mbar_wait(bars + 32 + 8 * wg, 0);
#pragma unroll
    for (int j = 0; j < 24; ++j) { xr[2 * j] = *reinterpret_cast<const uint32_t*>(p0 + 16 * j); xr[2 * j + 1] = *reinterpret_cast<const uint32_t*>(p1 + 16 * j); }
  }
  wg_wait<0>();
  fence_regs(acc);
  PROF(1, wg, 7);
  {
    float s0 = 0.f, s1 = 0.f;
#pragma unroll
    for (int j = 0; j < 24; ++j) {
      const uint32_t a = pack_bf16(bf_lo(xr[2 * j]) + acc[4 * j], bf_hi(xr[2 * j]) + acc[4 * j + 1]);
      const uint32_t b = pack_bf16(bf_lo(xr[2 * j + 1]) + acc[4 * j + 2], bf_hi(xr[2 * j + 1]) + acc[4 * j + 3]);
      xr[2 * j] = a; xr[2 * j + 1] = b;
      acc[4 * j] = bf_lo(a); acc[4 * j + 1] = bf_hi(a); acc[4 * j + 2] = bf_lo(b); acc[4 * j + 3] = bf_hi(b);
      s0 += acc[4 * j] + acc[4 * j + 1];
      s1 += acc[4 * j + 2] + acc[4 * j + 3];
    }
    s0 += __shfl_xor_sync(0xffffffffu, s0, 1); s0 += __shfl_xor_sync(0xffffffffu, s0, 2);
    s1 += __shfl_xor_sync(0xffffffffu, s1, 1); s1 += __shfl_xor_sync(0xffffffffu, s1, 2);
    const float mean0 = s0 * (1.f / 192.f), mean1 = s1 * (1.f / 192.f);
    float q0 = 0.f, q1 = 0.f;
#pragma unroll
    for (int j = 0; j < 24; ++j) {
      acc[4 * j] -= mean0; acc[4 * j + 1] -= mean0; acc[4 * j + 2] -= mean1; acc[4 * j + 3] -= mean1;
      q0 += acc[4 * j] * acc[4 * j] + acc[4 * j + 1] * acc[4 * j + 1];
      q1 += acc[4 * j + 2] * acc[4 * j + 2] + acc[4 * j + 3] * acc[4 * j + 3];
    }
    q0 += __shfl_xor_sync(0xffffffffu, q0, 1); q0 += __shfl_xor_sync(0xffffffffu, q0, 2);
    q1 += __shfl_xor_sync(0xffffffffu, q1, 1); q1 += __shfl_xor_sync(0xffffffffu, q1, 2);
    const float rs0 = 1.f / sqrtf(q0 * (1.f / 192.f) + 1e-5f), rs1 = 1.f / sqrtf(q1 * (1.f / 192.f) + 1e-5f);
#pragma unroll
    for (int j = 0; j < 24; ++j) {
      af[2 * j] = pack_bf16(acc[4 * j] * rs0, acc[4 * j + 1] * rs0);
      af[2 * j + 1] = pack_bf16(acc[4 * j + 2] * rs1, acc[4 * j + 3] * rs1);
    }
  }
  PROF(1, wg, 8);
  mbar_wait(bars + 16, 0);
  PROF(1, wg, 9);
  gemm_rs_w(acc, af, sWA, sWA + WCH, sWA + 2 * WCH);
  const int lrow = wl * 16 + ((lane >> 3) & 1) * 8 + (lane & 7), uh = lane >> 4;
  const int lj = lrow / 7, lt = lrow - lj * 7;
  const bool lvalid = lrow < 63;
  const uint32_t offX = lvalid ? (uint32_t)(lt * FS + lj * 384 + uh * 16) : 3456u;
  const uint32_t offH = lvalid ? (uint32_t)(lt * FS + lj * 128) : 3456u;
  const int lph = (n0 + lj) & 7;
  const uint32_t sStH = sWB + wg * TILE_BYTES;
  PROF(1, wg, 12);
  named_bar(3, 256);
  PROF(1, wg, 13);
#pragma unroll
  for (int i = 0; i < 12; ++i) {
    stsm_x4(sHt + offX + (lvalid ? i * 32 : 0), xr[4 * i], xr[4 * i + 1], xr[4 * i + 2], xr[4 * i + 3]);
    const int u = 2 * i + uh;
    stsm_x4(sStH + offH + (lvalid ? (uint32_t)((u >> 3) * 1152 + (((u ^ lph) & 7) << 4)) : 0u), af[4 * i], af[4 * i + 1], af[4 * i + 2], af[4 * i + 3]);
  }
  PROF(1, wg, 14);
  named_bar(1 + wg, 128);
  PROF(1, wg, 15);
  {
    const uint8_t* pStH = sptr + W_BYTES + wg * TILE_BYTES;
#pragma unroll 4
    for (int it = 0; it < 12; ++it) {
      const int idx = it * 128 + t;
      if (idx < 1512) {
        const int i = idx / 72, off = idx - i * 72, tt = i / 3, ch = i - tt * 3;
        const int so = tt * FS + ch * 1152 + off * 16;
        const uint4 a = *reinterpret_cast<const uint4*>(pHt + so), b = *reinterpret_cast<const uint4*>(pStH + so);
        reinterpret_cast<uint4*>(g_x1 + ((size_t)tt * N_ + n0) * C_)[ch * 72 + off] = a;
        reinterpret_cast<uint4*>(g_h2 + ((size_t)i * N_ + n0) * 64)[off] = b;
      }
    }
  }
  PROF(1, wg, 16);
  wg_wait<0>();
  fence_regs(acc);
  PROF(1, wg, 10);
#pragma unroll
  for (int i = 0; i < 48; ++i) af[i] = pack_bf16(acc[2 * i], acc[2 * i + 1]);
  named_bar(1 + wg, 128);
#pragma unroll
  for (int i = 0; i < 12; ++i) {
    const int u = 2 * i + uh;
    stsm_x4(sHt + offH + (lvalid ? (uint32_t)((u >> 3) * 1152 + (((u ^ lph) & 7) << 4)) : 0u), af[4 * i], af[4 * i + 1], af[4 * i + 2], af[4 * i + 3]);
  }
  named_bar(1 + wg, 128);
#pragma unroll 4
  for (int it = 0; it < 12; ++it) {
    const int idx = it * 128 + t;
    if (idx < 1512) {
      const int i = idx / 72, off = idx - i * 72, tt = i / 3, ch = i - tt * 3;
      reinterpret_cast<uint4*>(g_q2 + ((size_t)i * N_ + n0) * 64)[off] = *reinterpret_cast<const uint4*>(pHt + tt * FS + ch * 1152 + off * 16);
    }
  }
  PROF(1, wg, 11);
}

constexpr int KB = 144;
constexpr int KCH = KB * 128;
constexpr int STAGE_BYTES = 3 * KCH;
constexpr int NSTAGE = 3;
constexpr int P2_Q_OFF = NSTAGE * STAGE_BYTES;
constexpr int P2_ML_OFF = P2_Q_OFF + 2 * TILE_BYTES;
constexpr int P2_BAR_OFF = P2_ML_OFF + 2048;
constexpr int P2_SMEM = P2_BAR_OFF + 128 + 1024;
enum { K_EXCH = 0, K_PART_L = 1, K_PART_U = 2 };

struct Work { int f0, q0, b0, n0, f1, q1, b1, n1; };
__device__ __forceinline__ int u_lo(int u) { return (u * 21) >> 2; }
__device__ __forceinline__ Work get_work(int cl, int rank, int w) {
  Work k;
  if (cl < 63) {
    const int f = cl / 9, c = cl - f * 9;
    k.f0 = k.f1 = f;
    if (rank == 0) { k.q0 = 128 * c + 64 * w; k.b0 = 0; k.n0 = 5; k.q1 = 0; k.b1 = 0; k.n1 = 0; }
    else { k.q0 = 1152 + 64 * w; k.b0 = c; k.n0 = 1; k.q1 = 128 * c + 64 * w; k.b1 = 5; k.n1 = 4; }
  } else {
    const int u = ((cl - 63) * 2 + rank) * 2 + w;
    const int lo = u_lo(u), hi = u_lo(u + 1);
    const int f0 = lo / 9;
    const int mid = min(hi, 9 * (f0 + 1));
    k.q0 = k.q1 = 1280; k.f0 = f0; k.b0 = lo - 9 * f0; k.n0 = mid - lo; k.f1 = f0 + 1; k.b1 = 0; k.n1 = hi - mid;
  }
  return k;
}

constexpr int OPITCH = 400;
__device__ __forceinline__ uint32_t add_bf2(uint32_t a, uint32_t b) { return pack_bf16(bf_lo(a) + bf_lo(b), bf_hi(a) + bf_hi(b)); }

__global__ void __cluster_dims__(2, 1, 1) __launch_bounds__(384, 1) p2_kernel(__nv_bfloat16* __restrict__ out) {
  extern __shared__ uint8_t smem_raw[];
  const uint32_t sbase = (smem_u32(smem_raw) + 1023) & ~1023u;
  uint8_t* sptr = smem_raw + (sbase - smem_u32(smem_raw));
  const uint32_t sQ = sbase + P2_Q_OFF, sML = sbase + P2_ML_OFF, bars = sbase + P2_BAR_OFF;
  const uint32_t bFull = bars, bEmpty = bars + 24, bQFull = bars + 48, bQEmpty = bars + 64, bW = bars + 80, bXFree = bars + 88, bXFull = bars + 96;
  const int tid = threadIdx.x, lane = tid & 31;
  const int warp = __shfl_sync(0xffffffffu, tid >> 5, 0);
  const int cl = blockIdx.x >> 1, rank = blockIdx.x & 1;
  const bool modeB = cl >= 63;
  if (tid == 0) PROF(2, 3, 0);
  if (tid == 0) {
    for (int i = 0; i < NSTAGE; ++i) { mbar_init(bFull + 8 * i, 1); mbar_init(bEmpty + 8 * i, modeB ? 4 : 8); }
    for (int i = 0; i < 2; ++i) { mbar_init(bQFull + 8 * i, 1); mbar_init(bQEmpty + 8 * i, 4); }
    mbar_init(bW, 1); mbar_init(bXFree, 8); mbar_init(bXFull, 1);
    mbar_expect_tx(bXFull, 25 * 128 * 16);
    fence_mbar_init();
  }
  const Work wk0 = get_work(cl, rank, 0), wk1 = get_work(cl, rank, 1);
  const int nb0 = wk0.n0 + wk0.n1, nb1 = wk1.n0 + wk1.n1;
  const int firstW = (modeB && nb1 > nb0) ? 1 : 0;
  const int ntot = modeB ? nb0 + nb1 : nb0;
  const uint32_t sW0 = sbase + (ntot % NSTAGE) * STAGE_BYTES, sW1 = sW0 + WCH, sW2 = sbase + ((ntot + 1) % NSTAGE) * STAGE_BYTES;
  cluster_sync_all();
  pdl_wait();
  if (blockIdx.x == 0 && tid < 4) g_cnt[16 + tid] = 0;

  if (warp >= 8) {
    asm volatile("setmaxnreg.dec.sync.aligned.u32 40;");
    if (warp == 8 && lane == 0) {
#pragma unroll 1
      for (int i = 0; i < ntot; ++i) {
        const bool w1 = modeB && ((firstW + i) & 1);
        const int k = modeB ? (i >> 1) : i;
        const int n0 = w1 ? wk1.n0 : wk0.n0;
        const int f = (k < n0) ? (w1 ? wk1.f0 : wk0.f0) : (w1 ? wk1.f1 : wk0.f1);
        const int blk = (k < n0) ? ((w1 ? wk1.b0 : wk0.b0) + k) : ((w1 ? wk1.b1 : wk0.b1) + k - n0);
        const int st = i % NSTAGE;
        if (i >= NSTAGE) mbar_wait(bEmpty + 8 * st, ((i / NSTAGE) - 1) & 1);
        mbar_expect_tx(bFull + 8 * st, STAGE_BYTES);
        const __nv_bfloat16* src = g_h2 + (size_t)(f * 3) * (N_ * 64) + (size_t)blk * KB * 64;
#pragma unroll
        for (int ch = 0; ch < 3; ++ch) bulk_g2s(sbase + st * STAGE_BYTES + ch * KCH, src + (size_t)ch * (N_ * 64), KCH, bFull + 8 * st);
      }
      const __nv_bfloat16* wsrc = g_w + 3 * 3 * 192 * 64;
      mbar_expect_tx(bW, W_BYTES);
      mbar_wait(bEmpty + 8 * (ntot % NSTAGE), ((ntot / NSTAGE) - 1) & 1);
      bulk_g2s(sW0, wsrc, 2 * WCH, bW);
      mbar_wait(bEmpty + 8 * ((ntot + 1) % NSTAGE), (((ntot + 1) / NSTAGE) - 1) & 1);
      bulk_g2s(sW2, wsrc + 2 * 192 * 64, WCH, bW);
    } else if (warp == 9 && lane == 0) {
#pragma unroll 1
      for (int i = 0; i < 4; ++i) {
        const int sg = i >> 1, w = i & 1;
        const int n1 = w ? wk1.n1 : wk0.n1;
        if (sg && n1 == 0) continue;
        const int f = sg ? (w ? wk1.f1 : wk0.f1) : (w ? wk1.f0 : wk0.f0);
        const int qr = sg ? (w ? wk1.q1 : wk0.q1) : (w ? wk1.q0 : wk0.q0);
        if (sg) mbar_wait(bQEmpty + 8 * w, 0);
        mbar_expect_tx(bQFull + 8 * w, TILE_BYTES);
        const __nv_bfloat16* src = g_q2 + (size_t)(f * 3) * (N_ * 64) + (size_t)qr * 64;
#pragma unroll
        for (int ch = 0; ch < 3; ++ch) bulk_g2s(sQ + w * TILE_BYTES + ch * 8192, src + (size_t)ch * (N_ * 64), 8192, bQFull + 8 * w);
      }
    }
    return;
  }

  asm volatile("setmaxnreg.inc.sync.aligned.u32 232;");
  const int w = warp >> 2, wl = warp & 3, t = tid & 127;
  const int g = lane >> 2, q = lane & 3;
  const int r0 = wl * 16 + g;
  const uint32_t sQt = sQ + w * TILE_BYTES;
  const Work wk = w ? wk1 : wk0;
  const int nseg = wk.n1 ? 2 : 1;
  const int uidx = ((cl - 63) * 2 + rank) * 2 + w;
  const int nphase = nb0 + nseg;
  int phase = 0;
  if (w == 1 && !modeB) named_arrive(4, 256);
  PROF(2, w, 0);
  float o[96];
  float m0, m1, l0, l1;
  int k = 0;
  unsigned int* pend = nullptr;
  const uint64_t dQ = make_desc(sQt, 16, 1024);
#pragma unroll 1
  for (int sg = 0; sg < nseg; ++sg) {
    const int nblk = sg ? wk.n1 : wk.n0;
    const bool last = (sg + 1 == nseg);
    mbar_wait(bQFull + 8 * w, sg);
    if (sg == 0) PROF(2, w, 1);
    m0 = m1 = -INFINITY; l0 = l1 = 0.f;
    uint32_t pf[36];
    uint32_t sKprev = 0, bEprev = 0;
#pragma unroll 1
    for (int b = 0; b <= nblk; ++b) {
      uint32_t sK = sbase, bE = 0;
      if (b < nblk) {
        const int i = modeB ? (2 * k + ((w - firstW) & 1)) : k;
        const int st = i % NSTAGE;
        sK = sbase + st * STAGE_BYTES; bE = bEmpty + 8 * st;
        mbar_wait(bFull + 8 * st, (i / NSTAGE) & 1);
        PROF(2, w, 2 + 3 * k);
      }
      const uint64_t dK = make_desc(sK, 16, 1024), dV = make_desc(sKprev, KCH, 1024);
      float sc[72];
      if (!modeB) named_bar(4 + w, 256);
      if (b > 0) {
        wg_fence();
#pragma unroll
        for (int kk = 0; kk < 9; ++kk)
          wgmma_rs_n192<1>(o, pf[4 * kk], pf[4 * kk + 1], pf[4 * kk + 2], pf[4 * kk + 3], dV + kk * 128, (b > 1) || (kk > 0));
        wg_commit();
      }
      if (b < nblk) {
        if (b > 0) {
          wg_wait<0>();
          fence_regs(o);
          if (lane == 0) mbar_arrive(bEprev);
        }
        wg_fence();
#pragma unroll
        for (int kk = 0; kk < 12; ++kk)
          wgmma_ss_n144<0>(sc, dQ + ((kk >> 2) * 512 + (kk & 3) * 2), dK + ((kk >> 2) * (KCH / 16) + (kk & 3) * 2), kk > 0);
        wg_commit();
      }
      ++phase;
      if (!modeB && (w == 0 || phase < nphase)) named_arrive(4 + (w ^ 1), 256);
      wg_wait<0>();
      if (b == nblk) {
        fence_regs(o);
        if (lane == 0) mbar_arrive(bEprev);
        PROF(2, w, 1 + 3 * k);
        break;
      }
      fence_regs(sc);
      PROF(2, w, 3 + 3 * k);
      if (b == nblk - 1 && lane == 0) {
        if (!last) mbar_arrive(bQEmpty + 8 * w);
        else if (!modeB) mbar_arrive_remote(mapa(bXFree, rank ^ 1));
      }
      if (pend) {
        __threadfence();
        named_bar(1 + w, 128);
        if (t == 0) atomicAdd(pend, 1u);
        pend = nullptr;
      }
      float mx0 = sc[0], mx1 = sc[2];
#pragma unroll
      for (int j = 0; j < 18; ++j) {
        mx0 = fmaxf(mx0, fmaxf(sc[4 * j], sc[4 * j + 1]));
        mx1 = fmaxf(mx1, fmaxf(sc[4 * j + 2], sc[4 * j + 3]));
      }
      mx0 = fmaxf(mx0, __shfl_xor_sync(0xffffffffu, mx0, 1)); mx0 = fmaxf(mx0, __shfl_xor_sync(0xffffffffu, mx0, 2));
      mx1 = fmaxf(mx1, __shfl_xor_sync(0xffffffffu, mx1, 1)); mx1 = fmaxf(mx1, __shfl_xor_sync(0xffffffffu, mx1, 2));
      const float mn0 = fmaxf(m0, mx0), mn1 = fmaxf(m1, mx1);
      const float a0 = ex2((m0 - mn0) * SM_SCALE_LOG2), a1 = ex2((m1 - mn1) * SM_SCALE_LOG2);
      m0 = mn0; m1 = mn1;
      const float ms0 = mn0 * SM_SCALE_LOG2, ms1 = mn1 * SM_SCALE_LOG2;
      float ls0 = 0.f, ls1 = 0.f;
#pragma unroll
      for (int j = 0; j < 18; ++j) {
        const float p0 = ex2(fmaf(sc[4 * j], SM_SCALE_LOG2, -ms0)), p1 = ex2(fmaf(sc[4 * j + 1], SM_SCALE_LOG2, -ms0));
        const float p2 = ex2(fmaf(sc[4 * j + 2], SM_SCALE_LOG2, -ms1)), p3 = ex2(fmaf(sc[4 * j + 3], SM_SCALE_LOG2, -ms1));
        ls0 += p0 + p1; ls1 += p2 + p3;
        pf[2 * j] = pack_bf16(p0, p1);
        pf[2 * j + 1] = pack_bf16(p2, p3);
      }
      l0 = l0 * a0 + ls0; l1 = l1 * a1 + ls1;
      if (b > 0) {
#pragma unroll
        for (int j = 0; j < 24; ++j) { o[4 * j] *= a0; o[4 * j + 1] *= a0; o[4 * j + 2] *= a1; o[4 * j + 3] *= a1; }
      }
      sKprev = sK; bEprev = bE;
      ++k;
    }
    l0 += __shfl_xor_sync(0xffffffffu, l0, 1); l0 += __shfl_xor_sync(0xffffffffu, l0, 2);
    l1 += __shfl_xor_sync(0xffffffffu, l1, 1); l1 += __shfl_xor_sync(0xffffffffu, l1, 2);
    if (modeB || !last) {
      const int slot = modeB ? (126 + uidx * 2 + sg) : (cl * 2 + w);
      if (!modeB || wl == 0) {
        float4* po = reinterpret_cast<float4*>(g_part) + (size_t)slot * (24 * 128) + t;
#pragma unroll
        for (int j = 0; j < 24; ++j) po[j * 128] = make_float4(o[4 * j], o[4 * j + 1], o[4 * j + 2], o[4 * j + 3]);
        if (q == 0) {
          float2* pml = g_pml + slot * 64;
          pml[r0] = make_float2(m0, l0); pml[r0 + 8] = make_float2(m1, l1);
        }
      }
      pend = g_cnt + (modeB ? 8 + (sg ? wk.f1 : wk.f0) : wk.f0);
    }
  }
  if (pend) {
    __threadfence();
    named_bar(1 + w, 128);
    if (t == 0) atomicAdd(pend, 1u);
  }
  PROF(2, w, 20);

  const int f = wk.n1 ? wk.f1 : wk.f0;
  int kind = 0;
  uint32_t sT = sQt;
  int grow = f * N_;
  int np = 0, slot0 = 0, slab = 0;
  if (!modeB) {
    const int c = cl - f * 9;
    named_bar(3, 256);
    const uint32_t sLast = sbase + ((ntot + 2) % NSTAGE) * STAGE_BYTES;
    if (w != rank) {
      mbar_wait_cluster(bXFree, 0);
      const uint32_t rq = mapa(sQ, rank ^ 1) + t * 16, rb = mapa(bXFull, rank ^ 1);
#pragma unroll
      for (int i = 0; i < 24; ++i) st_async_v4(rq + i * 2048, o[4 * i], o[4 * i + 1], o[4 * i + 2], o[4 * i + 3], rb);
      st_async_v4(mapa(sML, rank ^ 1) + t * 16, m0, m1, l0, l1, rb);
      if (c < 8 && rank == (c & 1)) { kind = 2; np = 9; slot0 = f * 18 + (c >> 2); slab = c & 3; grow += 1152 + 16 * c; sT = sLast + TILE_BYTES; }
    } else {
      kind = 1; grow += wk.n1 ? wk.q1 : wk.q0; sT = sLast;
    }
  } else if (uidx == 0 || (u_lo(uidx) - 1) / 9 != f) {
    kind = 2; grow += 1280;
    int u0 = 0;
    while (u_lo(u0 + 1) <= 9 * f) ++u0;
    while (u0 + np < 12 && u_lo(u0 + np) < 9 * f + 9) ++np;
    slot0 = u0;
  }
  PROF(2, w, 21);
  if (kind == 0) return;
  uint8_t* pT = sptr + (sT - sbase);
  if (kind == 1) {
    mbar_wait_cluster(bXFull, 0);
    PROF(2, w, 17);
    const float4 ml = *reinterpret_cast<const float4*>(sptr + P2_ML_OFF + t * 16);
    const float mn0 = fmaxf(m0, ml.x), mn1 = fmaxf(m1, ml.y);
    float a0 = ex2((m0 - mn0) * SM_SCALE_LOG2), a1 = ex2((m1 - mn1) * SM_SCALE_LOG2);
    float b0 = ex2((ml.x - mn0) * SM_SCALE_LOG2), b1 = ex2((ml.y - mn1) * SM_SCALE_LOG2);
    const float i0 = 1.f / (a0 * l0 + b0 * ml.z), i1 = 1.f / (a1 * l1 + b1 * ml.w);
    a0 *= i0; b0 *= i0; a1 *= i1; b1 *= i1;
    const int lrow = wl * 16 + ((lane >> 3) & 1) * 8 + (lane & 7);
    const uint32_t ta = sT + lrow * 128;
#pragma unroll
    for (int i = 0; i < 12; ++i) {
      const float4 v0 = *reinterpret_cast<const float4*>(sptr + P2_Q_OFF + (2 * i) * 2048 + t * 16);
      const float4 v1 = *reinterpret_cast<const float4*>(sptr + P2_Q_OFF + (2 * i + 1) * 2048 + t * 16);
      const int u = 2 * i + (lane >> 4);
      stsm_x4(ta + (i >> 2) * 8192 + (((u ^ lrow) & 7) << 4),
              pack_bf16(a0 * o[8 * i] + b0 * v0.x, a0 * o[8 * i + 1] + b0 * v0.y), pack_bf16(a1 * o[8 * i + 2] + b1 * v0.z, a1 * o[8 * i + 3] + b1 * v0.w),
              pack_bf16(a0 * o[8 * i + 4] + b0 * v1.x, a0 * o[8 * i + 5] + b0 * v1.y), pack_bf16(a1 * o[8 * i + 6] + b1 * v1.z, a1 * o[8 * i + 7] + b1 * v1.w));
    }
  } else {
    if (t == 0) wait_counter(g_cnt + (modeB ? 8 : 0) + f, modeB ? np : 18);
    named_bar(1 + w, 128);
    __threadfence();
    float ma = -INFINITY, mb = -INFINITY, la = 0.f, lb = 0.f;
    float4 x[6];
#pragma unroll
    for (int j = 0; j < 6; ++j) x[j] = make_float4(0.f, 0.f, 0.f, 0.f);
#pragma unroll 1
    for (int i0 = 0; i0 < np; i0 += 3) {
      float4 v[3][6];
      float2 pa[3], pb[3];
#pragma unroll
      for (int i = 0; i < 3; ++i) {
        const int ii = min(i0 + i, np - 1);
        const int slot = modeB ? (126 + (slot0 + ii) * 2 + ((u_lo(slot0 + ii) / 9 == f) ? 0 : 1)) : (slot0 + 2 * ii);
        pa[i] = __ldcg(g_pml + slot * 64 + slab * 16 + g); pb[i] = __ldcg(g_pml + slot * 64 + slab * 16 + g + 8);
        if (i0 + i >= np) { pa[i].x = pb[i].x = -INFINITY; }
        const float4* src = reinterpret_cast<const float4*>(g_part) + (size_t)slot * (24 * 128) + (wl * 6) * 128 + slab * 32 + lane;
#pragma unroll
        for (int j = 0; j < 6; ++j) v[i][j] = __ldcg(src + j * 128);
      }
      const float na = fmaxf(fmaxf(ma, pa[0].x), fmaxf(pa[1].x, pa[2].x)), nb = fmaxf(fmaxf(mb, pb[0].x), fmaxf(pb[1].x, pb[2].x));
      const float sa = ex2((ma - na) * SM_SCALE_LOG2), sb = ex2((mb - nb) * SM_SCALE_LOG2);
      ma = na; mb = nb; la *= sa; lb *= sb;
#pragma unroll
      for (int j = 0; j < 6; ++j) { x[j].x *= sa; x[j].y *= sa; x[j].z *= sb; x[j].w *= sb; }
#pragma unroll
      for (int i = 0; i < 3; ++i) {
        const float wa = ex2((pa[i].x - na) * SM_SCALE_LOG2), wb = ex2((pb[i].x - nb) * SM_SCALE_LOG2);
        la += wa * pa[i].y; lb += wb * pb[i].y;
#pragma unroll
        for (int j = 0; j < 6; ++j) { x[j].x += wa * v[i][j].x; x[j].y += wa * v[i][j].y; x[j].z += wb * v[i][j].z; x[j].w += wb * v[i][j].w; }
      }
    }
    la = 1.f / la; lb = 1.f / lb;
#pragma unroll
    for (int j = 0; j < 6; ++j) {
      const int col = (wl * 6 + j) * 8 + 2 * q;
      uint8_t* ch = pT + (col >> 6) * 8192;
      *reinterpret_cast<uint32_t*>(ch + swz(g, col & 63) * 2) = pack_bf16(x[j].x * la, x[j].y * la);
      *reinterpret_cast<uint32_t*>(ch + swz(g + 8, col & 63) * 2) = pack_bf16(x[j].z * lb, x[j].w * lb);
    }
  }
  PROF(2, w, 18);
  fence_async_smem();
  named_bar(1 + w, 128);
  mbar_wait(bW, 0);
  PROF(2, w, 19);
  gemm_ss_w(o, sT, sW0, sW1, sW2);
  const int nit = (kind == 1) ? 12 : 3;
  uint4 xv[12];
  {
    const uint4* src = reinterpret_cast<const uint4*>(g_x1 + (size_t)grow * C_) + t;
#pragma unroll
    for (int it = 0; it < 12; ++it) if (it < nit) xv[it] = __ldcg(src + it * 128);
  }
  wg_wait<0>();
  fence_regs(o);
  PROF(2, w, 22);
  const uint32_t sS = (kind == 1) ? sQ : sT;
  if (kind == 1 || wl == 0) {
    const uint32_t addr = sS + (wl * 16 + ((lane >> 3) & 1) * 8 + (lane & 7)) * OPITCH + (lane >> 4) * 16;
#pragma unroll
    for (int i = 0; i < 12; ++i)
      stsm_x4(addr + i * 32, pack_bf16(o[8 * i], o[8 * i + 1]), pack_bf16(o[8 * i + 2], o[8 * i + 3]),
              pack_bf16(o[8 * i + 4], o[8 * i + 5]), pack_bf16(o[8 * i + 6], o[8 * i + 7]));
  }
  named_bar(1 + w, 128);
  {
    const uint8_t* pS = sptr + (sS - sbase);
    uint4* dst = reinterpret_cast<uint4*>(out + (size_t)grow * C_);
#pragma unroll
    for (int it = 0; it < 12; ++it) {
      if (it < nit) {
        const int unit = it * 128 + t, row = unit / 24, u = unit - row * 24;
        const uint4 y = *reinterpret_cast<const uint4*>(pS + row * OPITCH + u * 16);
        dst[unit] = make_uint4(add_bf2(xv[it].x, y.x), add_bf2(xv[it].y, y.y), add_bf2(xv[it].z, y.z), add_bf2(xv[it].w, y.w));
      }
    }
  }
  PROF(2, w, 23);
}

}

extern "C" void kernel_launch(void* const* d_in, const int* in_sizes, int n_in, void* d_out, int out_size) {
  using namespace tsf;
  const __nv_bfloat16* x = (const __nv_bfloat16*)d_in[0];
  const __nv_bfloat16* wqkv_t = (const __nv_bfloat16*)d_in[1];
  const __nv_bfloat16* wo_t = (const __nv_bfloat16*)d_in[2];
  const __nv_bfloat16* wqkv_s = (const __nv_bfloat16*)d_in[3];
  const __nv_bfloat16* wo_s = (const __nv_bfloat16*)d_in[4];
  __nv_bfloat16* out = (__nv_bfloat16*)d_out;
  static bool init = false;
  if (!init) {
    cudaFuncSetAttribute(p1_kernel, cudaFuncAttributeMaxDynamicSharedMemorySize, P1_SMEM);
    cudaFuncSetAttribute(p2_kernel, cudaFuncAttributeMaxDynamicSharedMemorySize, P2_SMEM);
    cudaFuncSetAttribute(p1_kernel, cudaFuncAttributePreferredSharedMemoryCarveout, cudaSharedmemCarveoutMaxShared);
    cudaFuncSetAttribute(p2_kernel, cudaFuncAttributePreferredSharedMemoryCarveout, cudaSharedmemCarveoutMaxShared);
    init = true;
  }
  cudaStream_t st = cudaStreamPerThread;
  p1_kernel<<<132, 384, P1_SMEM, st>>>(x, wqkv_t, wo_t, wqkv_s, wo_s);
  cudaLaunchAttribute at[1];
  at[0].id = cudaLaunchAttributeProgrammaticStreamSerialization;
  at[0].val.programmaticStreamSerializationAllowed = 1;
  {
    cudaLaunchConfig_t cfg = {};
    cfg.gridDim = dim3(132); cfg.blockDim = dim3(384); cfg.dynamicSmemBytes = P2_SMEM; cfg.stream = st;
    cfg.attrs = at; cfg.numAttrs = 1;
    cudaLaunchKernelEx(&cfg, p2_kernel, out);
  }
}
```

```cpp
#include <cuda_runtime.h>
#include <cuda_bf16.h>
#include <stdint.h>

namespace tsf {

constexpr int T_ = 7, N_ = 1296, C_ = 192, ROWS = T_ * N_;
constexpr float SM_SCALE_LOG2 = 0.07216878364870322f * 1.4426950408889634f;
constexpr uint32_t SPIN_LIMIT = 1u << 24;

__device__ __align__(1024) __nv_bfloat16 g_w[4 * 3 * 192 * 64];
__device__ __align__(1024) __nv_bfloat16 g_x1[ROWS * C_];
__device__ __align__(1024) __nv_bfloat16 g_h2[T_ * 3 * N_ * 64];
__device__ __align__(1024) __nv_bfloat16 g_q2[T_ * 3 * N_ * 64 + 64 * 64];
__device__ __align__(1024) uint4 g_part[189 * 12 * 128];
__device__ float4 g_pml[189 * 128];
__device__ unsigned int g_cnt[24];

#define PROF(kern, slot, idx)
__device__ __forceinline__ uint32_t smem_u32(const void* p) { return (uint32_t)__cvta_generic_to_shared(p); }
__device__ __forceinline__ void mbar_init(uint32_t bar, uint32_t count) {
  asm volatile("mbarrier.init.shared::cta.b64 [%0], %1;" ::"r"(bar), "r"(count) : "memory");
}
__device__ __forceinline__ void mbar_expect_tx(uint32_t bar, uint32_t bytes) {
  asm volatile("mbarrier.arrive.expect_tx.shared::cta.b64 _, [%0], %1;" ::"r"(bar), "r"(bytes) : "memory");
}
__device__ __forceinline__ void mbar_arrive(uint32_t bar) {
  asm volatile("mbarrier.arrive.shared::cta.b64 _, [%0];" ::"r"(bar) : "memory");
}
__device__ __forceinline__ void mbar_arrive_remote(uint32_t rbar) {
  asm volatile("mbarrier.arrive.release.cluster.shared::cluster.b64 _, [%0];" ::"r"(rbar) : "memory");
}
__device__ __forceinline__ bool mbar_try(uint32_t bar, uint32_t parity) {
  uint32_t ok;
  asm volatile("{\n.reg .pred p;\nmbarrier.try_wait.parity.shared::cta.b64 p, [%1], %2;\nselp.u32 %0, 1, 0, p;\n}\n"
               : "=r"(ok) : "r"(bar), "r"(parity) : "memory");
  return ok != 0;
}
__device__ __forceinline__ bool mbar_try_cluster(uint32_t bar, uint32_t parity) {
  uint32_t ok;
  asm volatile("{\n.reg .pred p;\nmbarrier.try_wait.parity.acquire.cluster.shared::cta.b64 p, [%1], %2;\nselp.u32 %0, 1, 0, p;\n}\n"
               : "=r"(ok) : "r"(bar), "r"(parity) : "memory");
  return ok != 0;
}
__device__ __forceinline__ void mbar_wait(uint32_t bar, uint32_t parity) {
#pragma unroll 1
  for (uint32_t it = 0; it < SPIN_LIMIT; ++it)
    if (mbar_try(bar, parity)) return;
  __trap();
}
__device__ __forceinline__ void mbar_wait_cluster(uint32_t bar, uint32_t parity) {
#pragma unroll 1
  for (uint32_t it = 0; it < SPIN_LIMIT; ++it)
    if (mbar_try_cluster(bar, parity)) return;
  __trap();
}
__device__ __forceinline__ void bulk_g2s(uint32_t dst, const void* src, uint32_t bytes, uint32_t bar) {
  asm volatile("cp.async.bulk.shared::cluster.global.mbarrier::complete_tx::bytes [%0], [%1], %2, [%3];"
               ::"r"(dst), "l"(src), "r"(bytes), "r"(bar) : "memory");
}
__device__ __forceinline__ void fence_async_smem() { asm volatile("fence.proxy.async.shared::cta;" ::: "memory"); }
__device__ __forceinline__ void fence_mbar_init() { asm volatile("fence.mbarrier_init.release.cluster;" ::: "memory"); }
__device__ __forceinline__ void named_bar(int id, int n) { asm volatile("bar.sync %0, %1;" ::"r"(id), "r"(n) : "memory"); }
__device__ __forceinline__ void wg_fence() { asm volatile("wgmma.fence.sync.aligned;" ::: "memory"); }
__device__ __forceinline__ void wg_commit() { asm volatile("wgmma.commit_group.sync.aligned;" ::: "memory"); }
template <int N> __device__ __forceinline__ void wg_wait() { asm volatile("wgmma.wait_group.sync.aligned %0;" ::"n"(N) : "memory"); }
template <int N> __device__ __forceinline__ void fence_regs(float (&d)[N]) {
#pragma unroll
  for (int i = 0; i < N; ++i) asm volatile("" : "+f"(d[i])::"memory");
}
__device__ __forceinline__ void pdl_wait() { asm volatile("griddepcontrol.wait;" ::: "memory"); }
__device__ __forceinline__ void pdl_launch() { asm volatile("griddepcontrol.launch_dependents;" ::: "memory"); }
__device__ __forceinline__ uint32_t mapa(uint32_t addr, uint32_t rank) {
  uint32_t r;
  asm volatile("mapa.shared::cluster.u32 %0, %1, %2;" : "=r"(r) : "r"(addr), "r"(rank));
  return r;
}
__device__ __forceinline__ void cluster_sync_all() {
  asm volatile("barrier.cluster.arrive.release.aligned;\nbarrier.cluster.wait.acquire.aligned;" ::: "memory");
}
__device__ __forceinline__ void st_cluster_v4(uint32_t addr, float a, float b, float c, float d) {
  asm volatile("st.shared::cluster.v4.f32 [%0], {%1, %2, %3, %4};" ::"r"(addr), "f"(a), "f"(b), "f"(c), "f"(d) : "memory");
}
__device__ __forceinline__ void st_async_v4(uint32_t addr, float a, float b, float c, float d, uint32_t rbar) {
  asm volatile("st.async.weak.shared::cluster.mbarrier::complete_tx::bytes.v4.f32 [%0], {%1, %2, %3, %4}, [%5];"
               ::"r"(addr), "f"(a), "f"(b), "f"(c), "f"(d), "r"(rbar) : "memory");
}
__device__ __forceinline__ uint32_t make_desc(uint32_t addr, uint32_t lbo, uint32_t) {
  return ((addr & 0x3FFFF) >> 4) | ((lbo >> 4) << 16);
}
__device__ __forceinline__ uint32_t pack_bf16(float lo, float hi) {
  uint32_t r;
  asm("cvt.rn.bf16x2.f32 %0, %1, %2;" : "=r"(r) : "f"(hi), "f"(lo));
  return r;
}
__device__ __forceinline__ float bf_lo(uint32_t v) { return __uint_as_float(v << 16); }
__device__ __forceinline__ float bf_hi(uint32_t v) { return __uint_as_float(v & 0xffff0000u); }
__device__ __forceinline__ float ex2(float x) {
  float r;
  asm("ex2.approx.ftz.f32 %0, %1;" : "=f"(r) : "f"(x));
  return r;
}
__device__ __forceinline__ void stsm_x4(uint32_t addr, uint32_t r0, uint32_t r1, uint32_t r2, uint32_t r3) {
  asm volatile("stmatrix.sync.aligned.m8n8.x4.shared.b16 [%0], {%1, %2, %3, %4};" ::"r"(addr), "r"(r0), "r"(r1), "r"(r2), "r"(r3) : "memory");
}
__device__ __forceinline__ void bulk_s2g(void* dst, uint32_t src, uint32_t bytes) {
  asm volatile("cp.async.bulk.global.shared::cta.bulk_group [%0], [%1], %2;" ::"l"(dst), "r"(src), "r"(bytes) : "memory");
}
__device__ __forceinline__ void bulk_commit() { asm volatile("cp.async.bulk.commit_group;" ::: "memory"); }
__device__ __forceinline__ void bulk_wait_read() { asm volatile("cp.async.bulk.wait_group.read 0;" ::: "memory"); }
__device__ __forceinline__ void bulk_wait_all() { asm volatile("cp.async.bulk.wait_group 0;" ::: "memory"); }
__device__ __forceinline__ void named_arrive(int id, int n) { asm volatile("bar.arrive %0, %1;" ::"r"(id), "r"(n) : "memory"); }
__device__ __forceinline__ void wait_counter(const unsigned int* p, unsigned int target) {
#pragma unroll 1
  for (uint32_t it = 0; it < SPIN_LIMIT; ++it) {
    unsigned int v;
    asm volatile("ld.acquire.gpu.global.u32 %0, [%1];" : "=r"(v) : "l"(p) : "memory");
    if (v >= target) return;
    __nanosleep(32);
  }
  __trap();
}
__device__ __forceinline__ void fence_async_all() { asm volatile("fence.proxy.async;" ::: "memory"); }
__device__ __forceinline__ int swz(int row, int col) { return row * 64 + ((((col >> 3) ^ row) & 7) << 3) + (col & 7); }

template <int TA, int TB>
__device__ __forceinline__ void wgmma_ss_n48(float (&d)[24], uint32_t da, uint32_t db, int sc) {
  asm volatile("{\n.reg .pred p;\n.reg .b64 da, db;\n.reg .b32 hi;\nmov.b32 hi, 0x40000040;\nmov.b64 da, {%24, hi};\nmov.b64 db, {%25, hi};\nsetp.ne.b32 p, %26, 0;\n"
    "wgmma.mma_async.sync.aligned.m64n48k16.f32.bf16.bf16 "
    "{%0, %1, %2, %3, %4, %5, %6, %7, %8, %9, %10, %11, %12, %13, %14, %15, %16, %17, %18, %19, %20, %21, %22, %23}, "
    "da, db, p, 1, 1, %27, %28;\n}\n"
    : "+f"(d[0]), "+f"(d[1]), "+f"(d[2]), "+f"(d[3]), "+f"(d[4]), "+f"(d[5]), "+f"(d[6]), "+f"(d[7]), "+f"(d[8]), "+f"(d[9]), "+f"(d[10]), "+f"(d[11]), "+f"(d[12]), "+f"(d[13]), "+f"(d[14]), "+f"(d[15]), "+f"(d[16]), "+f"(d[17]), "+f"(d[18]), "+f"(d[19]), "+f"(d[20]), "+f"(d[21]), "+f"(d[22]), "+f"(d[23])
    : "r"(da), "r"(db), "r"(sc), "n"(TA), "n"(TB));
}
template <int TA, int TB>
__device__ __forceinline__ void wgmma_ss_n192(float (&d)[96], uint32_t da, uint32_t db, int sc) {
  asm volatile("{\n.reg .pred p;\n.reg .b64 da, db;\n.reg .b32 hi;\nmov.b32 hi, 0x40000040;\nmov.b64 da, {%96, hi};\nmov.b64 db, {%97, hi};\nsetp.ne.b32 p, %98, 0;\n"
    "wgmma.mma_async.sync.aligned.m64n192k16.f32.bf16.bf16 "
    "{%0, %1, %2, %3, %4, %5, %6, %7, %8, %9, %10, %11, %12, %13, %14, %15, %16, %17, %18, %19, %20, %21, %22, %23, %24, %25, %26, %27, %28, %29, %30, %31, %32, %33, %34, %35, %36, %37, %38, %39, %40, %41, %42, %43, %44, %45, %46, %47, %48, %49, %50, %51, %52, %53, %54, %55, %56, %57, %58, %59, %60, %61, %62, %63, %64, %65, %66, %67, %68, %69, %70, %71, %72, %73, %74, %75, %76, %77, %78, %79, %80, %81, %82, %83, %84, %85, %86, %87, %88, %89, %90, %91, %92, %93, %94, %95}, "
    "da, db, p, 1, 1, %99, %100;\n}\n"
    : "+f"(d[0]), "+f"(d[1]), "+f"(d[2]), "+f"(d[3]), "+f"(d[4]), "+f"(d[5]), "+f"(d[6]), "+f"(d[7]), "+f"(d[8]), "+f"(d[9]), "+f"(d[10]), "+f"(d[11]), "+f"(d[12]), "+f"(d[13]), "+f"(d[14]), "+f"(d[15]), "+f"(d[16]), "+f"(d[17]), "+f"(d[18]), "+f"(d[19]), "+f"(d[20]), "+f"(d[21]), "+f"(d[22]), "+f"(d[23]), "+f"(d[24]), "+f"(d[25]), "+f"(d[26]), "+f"(d[27]), "+f"(d[28]), "+f"(d[29]), "+f"(d[30]), "+f"(d[31]), "+f"(d[32]), "+f"(d[33]), "+f"(d[34]), "+f"(d[35]), "+f"(d[36]), "+f"(d[37]), "+f"(d[38]), "+f"(d[39]), "+f"(d[40]), "+f"(d[41]), "+f"(d[42]), "+f"(d[43]), "+f"(d[44]), "+f"(d[45]), "+f"(d[46]), "+f"(d[47]), "+f"(d[48]), "+f"(d[49]), "+f"(d[50]), "+f"(d[51]), "+f"(d[52]), "+f"(d[53]), "+f"(d[54]), "+f"(d[55]), "+f"(d[56]), "+f"(d[57]), "+f"(d[58]), "+f"(d[59]), "+f"(d[60]), "+f"(d[61]), "+f"(d[62]), "+f"(d[63]), "+f"(d[64]), "+f"(d[65]), "+f"(d[66]), "+f"(d[67]), "+f"(d[68]), "+f"(d[69]), "+f"(d[70]), "+f"(d[71]), "+f"(d[72]), "+f"(d[73]), "+f"(d[74]), "+f"(d[75]), "+f"(d[76]), "+f"(d[77]), "+f"(d[78]), "+f"(d[79]), "+f"(d[80]), "+f"(d[81]), "+f"(d[82]), "+f"(d[83]), "+f"(d[84]), "+f"(d[85]), "+f"(d[86]), "+f"(d[87]), "+f"(d[88]), "+f"(d[89]), "+f"(d[90]), "+f"(d[91]), "+f"(d[92]), "+f"(d[93]), "+f"(d[94]), "+f"(d[95])
    : "r"(da), "r"(db), "r"(sc), "n"(TA), "n"(TB));
}
template <int TB>
__device__ __forceinline__ void wgmma_rs_n192(float (&d)[96], uint32_t a0, uint32_t a1, uint32_t a2, uint32_t a3, uint32_t db, int sc) {
  asm volatile("{\n.reg .pred p;\n.reg .b64 db;\n.reg .b32 hi;\nmov.b32 hi, 0x40000040;\nmov.b64 db, {%100, hi};\nsetp.ne.b32 p, %101, 0;\n"
    "wgmma.mma_async.sync.aligned.m64n192k16.f32.bf16.bf16 "
    "{%0, %1, %2, %3, %4, %5, %6, %7, %8, %9, %10, %11, %12, %13, %14, %15, %16, %17, %18, %19, %20, %21, %22, %23, %24, %25, %26, %27, %28, %29, %30, %31, %32, %33, %34, %35, %36, %37, %38, %39, %40, %41, %42, %43, %44, %45, %46, %47, %48, %49, %50, %51, %52, %53, %54, %55, %56, %57, %58, %59, %60, %61, %62, %63, %64, %65, %66, %67, %68, %69, %70, %71, %72, %73, %74, %75, %76, %77, %78, %79, %80, %81, %82, %83, %84, %85, %86, %87, %88, %89, %90, %91, %92, %93, %94, %95}, "
    "{%96, %97, %98, %99}, db, p, 1, 1, %102;\n}\n"
    : "+f"(d[0]), "+f"(d[1]), "+f"(d[2]), "+f"(d[3]), "+f"(d[4]), "+f"(d[5]), "+f"(d[6]), "+f"(d[7]), "+f"(d[8]), "+f"(d[9]), "+f"(d[10]), "+f"(d[11]), "+f"(d[12]), "+f"(d[13]), "+f"(d[14]), "+f"(d[15]), "+f"(d[16]), "+f"(d[17]), "+f"(d[18]), "+f"(d[19]), "+f"(d[20]), "+f"(d[21]), "+f"(d[22]), "+f"(d[23]), "+f"(d[24]), "+f"(d[25]), "+f"(d[26]), "+f"(d[27]), "+f"(d[28]), "+f"(d[29]), "+f"(d[30]), "+f"(d[31]), "+f"(d[32]), "+f"(d[33]), "+f"(d[34]), "+f"(d[35]), "+f"(d[36]), "+f"(d[37]), "+f"(d[38]), "+f"(d[39]), "+f"(d[40]), "+f"(d[41]), "+f"(d[42]), "+f"(d[43]), "+f"(d[44]), "+f"(d[45]), "+f"(d[46]), "+f"(d[47]), "+f"(d[48]), "+f"(d[49]), "+f"(d[50]), "+f"(d[51]), "+f"(d[52]), "+f"(d[53]), "+f"(d[54]), "+f"(d[55]), "+f"(d[56]), "+f"(d[57]), "+f"(d[58]), "+f"(d[59]), "+f"(d[60]), "+f"(d[61]), "+f"(d[62]), "+f"(d[63]), "+f"(d[64]), "+f"(d[65]), "+f"(d[66]), "+f"(d[67]), "+f"(d[68]), "+f"(d[69]), "+f"(d[70]), "+f"(d[71]), "+f"(d[72]), "+f"(d[73]), "+f"(d[74]), "+f"(d[75]), "+f"(d[76]), "+f"(d[77]), "+f"(d[78]), "+f"(d[79]), "+f"(d[80]), "+f"(d[81]), "+f"(d[82]), "+f"(d[83]), "+f"(d[84]), "+f"(d[85]), "+f"(d[86]), "+f"(d[87]), "+f"(d[88]), "+f"(d[89]), "+f"(d[90]), "+f"(d[91]), "+f"(d[92]), "+f"(d[93]), "+f"(d[94]), "+f"(d[95])
    : "r"(a0), "r"(a1), "r"(a2), "r"(a3), "r"(db), "r"(sc), "n"(TB));
}
template <int TB>
__device__ __forceinline__ void wgmma_rs_n64(float (&d)[32], uint32_t a0, uint32_t a1, uint32_t a2, uint32_t a3, uint32_t db, int sc) {
  asm volatile("{\n.reg .pred p;\n.reg .b64 db;\n.reg .b32 hi;\nmov.b32 hi, 0x40000040;\nmov.b64 db, {%36, hi};\nsetp.ne.b32 p, %37, 0;\n"
    "wgmma.mma_async.sync.aligned.m64n64k16.f32.bf16.bf16 "
    "{%0, %1, %2, %3, %4, %5, %6, %7, %8, %9, %10, %11, %12, %13, %14, %15, %16, %17, %18, %19, %20, %21, %22, %23, %24, %25, %26, %27, %28, %29, %30, %31}, "
    "{%32, %33, %34, %35}, db, p, 1, 1, %38;\n}\n"
    : "+f"(d[0]), "+f"(d[1]), "+f"(d[2]), "+f"(d[3]), "+f"(d[4]), "+f"(d[5]), "+f"(d[6]), "+f"(d[7]), "+f"(d[8]), "+f"(d[9]), "+f"(d[10]), "+f"(d[11]), "+f"(d[12]), "+f"(d[13]), "+f"(d[14]), "+f"(d[15]), "+f"(d[16]), "+f"(d[17]), "+f"(d[18]), "+f"(d[19]), "+f"(d[20]), "+f"(d[21]), "+f"(d[22]), "+f"(d[23]), "+f"(d[24]), "+f"(d[25]), "+f"(d[26]), "+f"(d[27]), "+f"(d[28]), "+f"(d[29]), "+f"(d[30]), "+f"(d[31])
    : "r"(a0), "r"(a1), "r"(a2), "r"(a3), "r"(db), "r"(sc), "n"(TB));
}
template <int TA, int TB>
__device__ __forceinline__ void wgmma_ss_n144(float (&d)[72], uint32_t da, uint32_t db, int sc) {
  asm volatile("{\n.reg .pred p;\n.reg .b64 da, db;\n.reg .b32 hi;\nmov.b32 hi, 0x40000040;\nmov.b64 da, {%72, hi};\nmov.b64 db, {%73, hi};\nsetp.ne.b32 p, %74, 0;\n"
    "wgmma.mma_async.sync.aligned.m64n144k16.f32.bf16.bf16 "
    "{%0, %1, %2, %3, %4, %5, %6, %7, %8, %9, %10, %11, %12, %13, %14, %15, %16, %17, %18, %19, %20, %21, %22, %23, %24, %25, %26, %27, %28, %29, %30, %31, %32, %33, %34, %35, %36, %37, %38, %39, %40, %41, %42, %43, %44, %45, %46, %47, %48, %49, %50, %51, %52, %53, %54, %55, %56, %57, %58, %59, %60, %61, %62, %63, %64, %65, %66, %67, %68, %69, %70, %71}, "
    "da, db, p, 1, 1, %75, %76;\n}\n"
    : "+f"(d[0]), "+f"(d[1]), "+f"(d[2]), "+f"(d[3]), "+f"(d[4]), "+f"(d[5]), "+f"(d[6]), "+f"(d[7]), "+f"(d[8]), "+f"(d[9]), "+f"(d[10]), "+f"(d[11]), "+f"(d[12]), "+f"(d[13]), "+f"(d[14]), "+f"(d[15]), "+f"(d[16]), "+f"(d[17]), "+f"(d[18]), "+f"(d[19]), "+f"(d[20]), "+f"(d[21]), "+f"(d[22]), "+f"(d[23]), "+f"(d[24]), "+f"(d[25]), "+f"(d[26]), "+f"(d[27]), "+f"(d[28]), "+f"(d[29]), "+f"(d[30]), "+f"(d[31]), "+f"(d[32]), "+f"(d[33]), "+f"(d[34]), "+f"(d[35]), "+f"(d[36]), "+f"(d[37]), "+f"(d[38]), "+f"(d[39]), "+f"(d[40]), "+f"(d[41]), "+f"(d[42]), "+f"(d[43]), "+f"(d[44]), "+f"(d[45]), "+f"(d[46]), "+f"(d[47]), "+f"(d[48]), "+f"(d[49]), "+f"(d[50]), "+f"(d[51]), "+f"(d[52]), "+f"(d[53]), "+f"(d[54]), "+f"(d[55]), "+f"(d[56]), "+f"(d[57]), "+f"(d[58]), "+f"(d[59]), "+f"(d[60]), "+f"(d[61]), "+f"(d[62]), "+f"(d[63]), "+f"(d[64]), "+f"(d[65]), "+f"(d[66]), "+f"(d[67]), "+f"(d[68]), "+f"(d[69]), "+f"(d[70]), "+f"(d[71])
    : "r"(da), "r"(db), "r"(sc), "n"(TA), "n"(TB));
}

__device__ __forceinline__ void fuse_weights(uint32_t sbase, uint8_t* sptr, int j, const __nv_bfloat16* __restrict__ wqkv_t,
                                             const __nv_bfloat16* __restrict__ wo_t, const __nv_bfloat16* __restrict__ wqkv_s,
                                             const __nv_bfloat16* __restrict__ wo_s) {
  const int m = j / 12, n0 = ((j % 12) >> 2) * 64, k0 = (j & 3) * 48;
  const __nv_bfloat16* wqkv = (m < 2) ? wqkv_t : wqkv_s;
  const __nv_bfloat16* wo = (m < 2) ? wo_t : wo_s;
  const int tid = threadIdx.x;
  const bool odd = m & 1;
  uint8_t* pA = sptr; uint8_t* pB = sptr + 24576;
  uint4 va[4], vb[3];
#pragma unroll
  for (int i = 0; i < 4; ++i) {
    const int u = tid + i * 384;
    const int row = odd ? (u >> 3) : (u / 24), cu = odd ? (u & 7) : (u % 24);
    va[i] = __ldg(reinterpret_cast<const uint4*>(odd ? (wo + row * 192 + n0 + cu * 8) : (wqkv + (n0 + row) * 576 + 192 + cu * 8)));
  }
#pragma unroll
  for (int i = 0; i < 3; ++i) {
    const int u = tid + i * 384, row = u / 24, cu = u % 24;
    vb[i] = __ldg(reinterpret_cast<const uint4*>(wqkv + (k0 + row) * 576 + (odd ? 384 : 0) + cu * 8));
  }
#pragma unroll
  for (int i = 0; i < 4; ++i) {
    const int u = tid + i * 384;
    const int row = odd ? (u >> 3) : (u / 24), cu = odd ? (u & 7) : (u % 24);
    *reinterpret_cast<uint4*>(pA + (cu >> 3) * 8192 + row * 128 + (((cu ^ row) & 7) << 4)) = va[i];
  }
#pragma unroll
  for (int i = 0; i < 3; ++i) {
    const int u = tid + i * 384, row = u / 24, cu = u % 24;
    *reinterpret_cast<uint4*>(pB + (cu >> 3) * 6144 + row * 128 + (((cu ^ row) & 7) << 4)) = vb[i];
  }
  fence_async_smem();
  __syncthreads();
  if (tid < 128) {
    float acc[24];
    const uint32_t dB = make_desc(sbase + 24576, 16, 1024);
    wg_fence();
    if (odd) {
      const uint32_t dA = make_desc(sbase, 8192, 1024);
#pragma unroll
      for (int kk = 0; kk < 12; ++kk) wgmma_ss_n48<1, 0>(acc, dA + kk * 128, dB + ((kk >> 2) * 384 + (kk & 3) * 2), kk > 0);
    } else {
      const uint32_t dA = make_desc(sbase, 16, 1024);
#pragma unroll
      for (int kk = 0; kk < 12; ++kk) wgmma_ss_n48<0, 0>(acc, dA + ((kk >> 2) * 512 + (kk & 3) * 2), dB + ((kk >> 2) * 384 + (kk & 3) * 2), kk > 0);
    }
    wg_commit();
    wg_wait<0>();
    fence_regs(acc);
    const int lane = tid & 31, r0 = n0 + (tid >> 5) * 16 + (lane >> 2);
    __nv_bfloat16* dst = g_w + (size_t)m * 3 * 192 * 64;
#pragma unroll
    for (int jj = 0; jj < 6; ++jj) {
      const int k = k0 + 8 * jj + 2 * (lane & 3);
      __nv_bfloat16* ch = dst + (k >> 6) * (192 * 64);
      *reinterpret_cast<uint32_t*>(ch + swz(r0, k & 63)) = pack_bf16(acc[4 * jj], acc[4 * jj + 1]);
      *reinterpret_cast<uint32_t*>(ch + swz(r0 + 8, k & 63)) = pack_bf16(acc[4 * jj + 2], acc[4 * jj + 3]);
    }
    __threadfence();
    named_bar(1, 128);
    if (tid == 0) atomicAdd(g_cnt + 16 + m, 1u);
  }
}

constexpr int W_BYTES = 3 * 192 * 128;
constexpr int WCH = 192 * 128;
constexpr int TILE_BYTES = 3 * 64 * 128;
constexpr int P1_SMEM = 2 * W_BYTES + 2 * TILE_BYTES + 128 + 1024;

__device__ __forceinline__ void gemm_rs_w(float (&acc)[96], const uint32_t (&a)[48], uint32_t c0, uint32_t c1, uint32_t c2) {
  wg_fence();
#pragma unroll
  for (int kk = 0; kk < 12; ++kk) {
    const uint32_t base = (kk < 4) ? c0 : ((kk < 8) ? c1 : c2);
    wgmma_rs_n192<0>(acc, a[4 * kk], a[4 * kk + 1], a[4 * kk + 2], a[4 * kk + 3], make_desc(base + (kk & 3) * 32, 16, 1024), kk > 0);
  }
  wg_commit();
}
__device__ __forceinline__ void gemm_ss_w(float (&acc)[96], uint32_t atile, uint32_t c0, uint32_t c1, uint32_t c2) {
  wg_fence();
#pragma unroll
  for (int kk = 0; kk < 12; ++kk) {
    const uint32_t base = (kk < 4) ? c0 : ((kk < 8) ? c1 : c2);
    wgmma_ss_n192<0, 0>(acc, make_desc(atile + (kk >> 2) * 8192 + (kk & 3) * 32, 16, 1024), make_desc(base + (kk & 3) * 32, 16, 1024), kk > 0);
  }
  wg_commit();
}

__global__ void __launch_bounds__(384, 1) p1_kernel(const __nv_bfloat16* __restrict__ x, const __nv_bfloat16* __restrict__ wqkv_t,
                                                    const __nv_bfloat16* __restrict__ wo_t, const __nv_bfloat16* __restrict__ wqkv_s,
                                                    const __nv_bfloat16* __restrict__ wo_s) {
  extern __shared__ uint8_t smem_raw[];
  const uint32_t sbase = (smem_u32(smem_raw) + 1023) & ~1023u;
  uint8_t* sptr = smem_raw + (sbase - smem_u32(smem_raw));
  if (blockIdx.x >= 72) {
    PROF(0, 0, 0);
    pdl_launch();
    if (blockIdx.x == 131 && threadIdx.x < 16) g_cnt[threadIdx.x] = 0;
    if (blockIdx.x < 120) fuse_weights(sbase, sptr, blockIdx.x - 72, wqkv_t, wo_t, wqkv_s, wo_s);
    PROF(0, 0, 1);
    return;
  }
  const uint32_t sWA = sbase, sWB = sbase + W_BYTES, sH = sbase + 2 * W_BYTES;
  const uint32_t bars = sH + 2 * TILE_BYTES;
  const int tid = threadIdx.x, warp = tid >> 5, lane = tid & 31;
  if (tid == 0) PROF(1, 3, 0);
  pdl_launch();
  if (tid == 0) {
    mbar_init(bars, 1); mbar_init(bars + 8, 1); mbar_init(bars + 16, 1); mbar_init(bars + 24, 8); mbar_init(bars + 32, 4); mbar_init(bars + 40, 4);
    fence_mbar_init();
  }
  __syncthreads();

  if (warp >= 8) {
    asm volatile("setmaxnreg.dec.sync.aligned.u32 40;");
    if (warp == 8 && lane == 0) {
      wait_counter(g_cnt + 16, 12);
      fence_async_all();
      mbar_expect_tx(bars, W_BYTES);
      bulk_g2s(sWA, g_w, W_BYTES, bars);
      wait_counter(g_cnt + 17, 12);
      fence_async_all();
      mbar_expect_tx(bars + 8, W_BYTES);
      bulk_g2s(sWB, g_w + 3 * 192 * 64, W_BYTES, bars + 8);
      wait_counter(g_cnt + 18, 12);
      fence_async_all();
      mbar_wait(bars + 24, 0);
      mbar_expect_tx(bars + 16, W_BYTES);
      bulk_g2s(sWA, g_w + 2 * 3 * 192 * 64, W_BYTES, bars + 16);
    }
    return;
  }

  asm volatile("setmaxnreg.inc.sync.aligned.u32 232;");
  const int wg = warp >> 2, t = tid & 127, wl = warp & 3;
  const int n0 = (blockIdx.x * 2 + wg) * 9;
  const uint32_t sHt = sH + wg * TILE_BYTES;
  PROF(1, wg, 0);
  uint8_t* pHt = sptr + 2 * W_BYTES + wg * TILE_BYTES;
  {
    const int row = t >> 1, half = t & 1;
    uint4 v[12];
    if (row < 63) {
      const int j = row / 7, tt = row - j * 7;
      const uint4* src = reinterpret_cast<const uint4*>(x + ((size_t)tt * N_ + n0 + j) * C_ + half * 96);
#pragma unroll
      for (int i = 0; i < 12; ++i) v[i] = __ldg(src + i);
    } else {
#pragma unroll
      for (int i = 0; i < 12; ++i) v[i] = make_uint4(0, 0, 0, 0);
    }
    float s = 0.f;
#pragma unroll
    for (int i = 0; i < 12; ++i) {
      s += bf_lo(v[i].x) + bf_hi(v[i].x) + bf_lo(v[i].y) + bf_hi(v[i].y) + bf_lo(v[i].z) + bf_hi(v[i].z) + bf_lo(v[i].w) + bf_hi(v[i].w);
    }
    s += __shfl_xor_sync(0xffffffffu, s, 1);
    const float mean = s * (1.f / 192.f);
    float ss = 0.f;
#pragma unroll
    for (int i = 0; i < 12; ++i) {
      const uint32_t w4[4] = {v[i].x, v[i].y, v[i].z, v[i].w};
#pragma unroll
      for (int e = 0; e < 4; ++e) {
        float a = bf_lo(w4[e]) - mean, b = bf_hi(w4[e]) - mean;
        ss += a * a + b * b;
      }
    }
    ss += __shfl_xor_sync(0xffffffffu, ss, 1);
    const float rstd = 1.f / sqrtf(ss * (1.f / 192.f) + 1e-5f);
#pragma unroll
    for (int i = 0; i < 12; ++i) {
      const uint32_t w4[4] = {v[i].x, v[i].y, v[i].z, v[i].w};
      uint32_t o4[4];
#pragma unroll
      for (int e = 0; e < 4; ++e) o4[e] = pack_bf16((bf_lo(w4[e]) - mean) * rstd, (bf_hi(w4[e]) - mean) * rstd);
      const int col = half * 96 + i * 8;
      *reinterpret_cast<uint4*>(pHt + (col >> 6) * 8192 + row * 128 + ((((col >> 3) ^ row) & 7) << 4)) = make_uint4(o4[0], o4[1], o4[2], o4[3]);
    }
  }
  PROF(1, wg, 1);
  fence_async_smem();
  named_bar(1 + wg, 128);

  const int g = lane >> 2, q = lane & 3;
  const int r0 = wl * 16 + g, r1 = r0 + 8;
  float acc[96];
  uint32_t af[48];
  mbar_wait(bars, 0);
  PROF(1, wg, 2);
  gemm_ss_w(acc, sHt, sWA, sWA + WCH, sWA + 2 * WCH);
  wg_wait<0>();
  fence_regs(acc);
  PROF(1, wg, 3);
  if (lane == 0) mbar_arrive(bars + 24);
#pragma unroll
  for (int i = 0; i < 48; ++i) af[i] = pack_bf16(acc[2 * i], acc[2 * i + 1]);
  float sc[32];
  wg_fence();
#pragma unroll
  for (int kk = 0; kk < 12; ++kk)
    wgmma_rs_n64<0>(sc, af[4 * kk], af[4 * kk + 1], af[4 * kk + 2], af[4 * kk + 3],
                    make_desc(sHt + (kk >> 2) * 8192 + (kk & 3) * 32, 16, 1024), kk > 0);
  wg_commit();
  wg_wait<0>();
  fence_regs(sc);
  PROF(1, wg, 4);
  uint32_t pf[16];
  {
    const int g0 = r0 / 7, g1 = r1 / 7;
    float mx0 = -INFINITY, mx1 = -INFINITY;
#pragma unroll
    for (int j = 0; j < 8; ++j) {
#pragma unroll
      for (int e = 0; e < 2; ++e) {
        const int col = 8 * j + 2 * q + e;
        const int cg = col / 7;
        if (cg != g0) sc[4 * j + e] = -INFINITY;
        if (cg != g1) sc[4 * j + 2 + e] = -INFINITY;
        mx0 = fmaxf(mx0, sc[4 * j + e]);
        mx1 = fmaxf(mx1, sc[4 * j + 2 + e]);
      }
    }
    mx0 = fmaxf(mx0, __shfl_xor_sync(0xffffffffu, mx0, 1)); mx0 = fmaxf(mx0, __shfl_xor_sync(0xffffffffu, mx0, 2));
    mx1 = fmaxf(mx1, __shfl_xor_sync(0xffffffffu, mx1, 1)); mx1 = fmaxf(mx1, __shfl_xor_sync(0xffffffffu, mx1, 2));
    float l0 = 0.f, l1 = 0.f;
#pragma unroll
    for (int j = 0; j < 8; ++j) {
#pragma unroll
      for (int e = 0; e < 2; ++e) {
        sc[4 * j + e] = ex2((sc[4 * j + e] - mx0) * SM_SCALE_LOG2);
        sc[4 * j + 2 + e] = ex2((sc[4 * j + 2 + e] - mx1) * SM_SCALE_LOG2);
        l0 += sc[4 * j + e];
        l1 += sc[4 * j + 2 + e];
      }
    }
    l0 += __shfl_xor_sync(0xffffffffu, l0, 1); l0 += __shfl_xor_sync(0xffffffffu, l0, 2);
    l1 += __shfl_xor_sync(0xffffffffu, l1, 1); l1 += __shfl_xor_sync(0xffffffffu, l1, 2);
    const float i0 = 1.f / l0, i1 = 1.f / l1;
#pragma unroll
    for (int j = 0; j < 8; ++j) {
      pf[2 * j] = pack_bf16(sc[4 * j] * i0, sc[4 * j + 1] * i0);
      pf[2 * j + 1] = pack_bf16(sc[4 * j + 2] * i1, sc[4 * j + 3] * i1);
    }
  }
  wg_fence();
#pragma unroll
  for (int kk = 0; kk < 4; ++kk)
    wgmma_rs_n192<1>(acc, pf[4 * kk], pf[4 * kk + 1], pf[4 * kk + 2], pf[4 * kk + 3], make_desc(sHt + kk * 2048, 8192, 1024), kk > 0);
  wg_commit();
  wg_wait<0>();
  fence_regs(acc);
#pragma unroll
  for (int i = 0; i < 48; ++i) af[i] = pack_bf16(acc[2 * i], acc[2 * i + 1]);
  PROF(1, wg, 5);
  constexpr int FS = 3472;
  named_bar(1 + wg, 128);
  if (lane == 0) {
    mbar_expect_tx(bars + 32 + 8 * wg, (wl == 3 ? 1 : 2) * 3456);
#pragma unroll 1
    for (int tt = wl; tt < 7; tt += 4) bulk_g2s(sHt + tt * FS, x + ((size_t)tt * N_ + n0) * C_, 3456, bars + 32 + 8 * wg);
  }
  mbar_wait(bars + 8, 0);
  PROF(1, wg, 6);
  gemm_rs_w(acc, af, sWB, sWB + WCH, sWB + 2 * WCH);
  uint32_t xr[48];
  {
    const int j0 = r0 / 7, t0 = r0 - j0 * 7, j1 = min(r1, 62) / 7, t1 = min(r1, 62) - j1 * 7;
    const uint8_t* p0 = pHt + t0 * FS + j0 * 384 + q * 4;
    const uint8_t* p1 = pHt + t1 * FS + j1 * 384 + q * 4;
    mbar_wait(bars + 32 + 8 * wg, 0);
#pragma unroll
    for (int j = 0; j < 24; ++j) { xr[2 * j] = *reinterpret_cast<const uint32_t*>(p0 + 16 * j); xr[2 * j + 1] = *reinterpret_cast<const uint32_t*>(p1 + 16 * j); }
  }
  wg_wait<0>();
  fence_regs(acc);
  PROF(1, wg, 7);
  {
    float s0 = 0.f, s1 = 0.f;
#pragma unroll
    for (int j = 0; j < 24; ++j) {
      const uint32_t a = pack_bf16(bf_lo(xr[2 * j]) + acc[4 * j], bf_hi(xr[2 * j]) + acc[4 * j + 1]);
      const uint32_t b = pack_bf16(bf_lo(xr[2 * j + 1]) + acc[4 * j + 2], bf_hi(xr[2 * j + 1]) + acc[4 * j + 3]);
      xr[2 * j] = a; xr[2 * j + 1] = b;
      acc[4 * j] = bf_lo(a); acc[4 * j + 1] = bf_hi(a); acc[4 * j + 2] = bf_lo(b); acc[4 * j + 3] = bf_hi(b);
      s0 += acc[4 * j] + acc[4 * j + 1];
      s1 += acc[4 * j + 2] + acc[4 * j + 3];
    }
    s0 += __shfl_xor_sync(0xffffffffu, s0, 1); s0 += __shfl_xor_sync(0xffffffffu, s0, 2);
    s1 += __shfl_xor_sync(0xffffffffu, s1, 1); s1 += __shfl_xor_sync(0xffffffffu, s1, 2);
    const float mean0 = s0 * (1.f / 192.f), mean1 = s1 * (1.f / 192.f);
    float q0 = 0.f, q1 = 0.f;
#pragma unroll
    for (int j = 0; j < 24; ++j) {
      acc[4 * j] -= mean0; acc[4 * j + 1] -= mean0; acc[4 * j + 2] -= mean1; acc[4 * j + 3] -= mean1;
      q0 += acc[4 * j] * acc[4 * j] + acc[4 * j + 1] * acc[4 * j + 1];
      q1 += acc[4 * j + 2] * acc[4 * j + 2] + acc[4 * j + 3] * acc[4 * j + 3];
    }
    q0 += __shfl_xor_sync(0xffffffffu, q0, 1); q0 += __shfl_xor_sync(0xffffffffu, q0, 2);
    q1 += __shfl_xor_sync(0xffffffffu, q1, 1); q1 += __shfl_xor_sync(0xffffffffu, q1, 2);
    const float rs0 = 1.f / sqrtf(q0 * (1.f / 192.f) + 1e-5f), rs1 = 1.f / sqrtf(q1 * (1.f / 192.f) + 1e-5f);
#pragma unroll
    for (int j = 0; j < 24; ++j) {
      af[2 * j] = pack_bf16(acc[4 * j] * rs0, acc[4 * j + 1] * rs0);
      af[2 * j + 1] = pack_bf16(acc[4 * j + 2] * rs1, acc[4 * j + 3] * rs1);
    }
  }
  PROF(1, wg, 8);
  mbar_wait(bars + 16, 0);
  PROF(1, wg, 9);
  gemm_rs_w(acc, af, sWA, sWA + WCH, sWA + 2 * WCH);
  const int lrow = wl * 16 + ((lane >> 3) & 1) * 8 + (lane & 7), uh = lane >> 4;
  const int lj = lrow / 7, lt = lrow - lj * 7;
  const bool lvalid = lrow < 63;
  const uint32_t offX = lvalid ? (uint32_t)(lt * FS + lj * 384 + uh * 16) : 3456u;
  const uint32_t offH = lvalid ? (uint32_t)(lt * FS + lj * 128) : 3456u;
  const int lph = (n0 + lj) & 7;
  const uint32_t sStH = sWB + wg * TILE_BYTES;
  PROF(1, wg, 12);
  named_bar(3, 256);
  PROF(1, wg, 13);
#pragma unroll
  for (int i = 0; i < 12; ++i) {
    stsm_x4(sHt + offX + (lvalid ? i * 32 : 0), xr[4 * i], xr[4 * i + 1], xr[4 * i + 2], xr[4 * i + 3]);
    const int u = 2 * i + uh;
    stsm_x4(sStH + offH + (lvalid ? (uint32_t)((u >> 3) * 1152 + (((u ^ lph) & 7) << 4)) : 0u), af[4 * i], af[4 * i + 1], af[4 * i + 2], af[4 * i + 3]);
  }
  PROF(1, wg, 14);
  named_bar(1 + wg, 128);
  PROF(1, wg, 15);
  {
    const uint8_t* pStH = sptr + W_BYTES + wg * TILE_BYTES;
#pragma unroll 4
    for (int it = 0; it < 12; ++it) {
      const int idx = it * 128 + t;
      if (idx < 1512) {
        const int i = idx / 72, off = idx - i * 72, tt = i / 3, ch = i - tt * 3;
        const int so = tt * FS + ch * 1152 + off * 16;
        const uint4 a = *reinterpret_cast<const uint4*>(pHt + so), b = *reinterpret_cast<const uint4*>(pStH + so);
        reinterpret_cast<uint4*>(g_x1 + ((size_t)tt * N_ + n0) * C_)[ch * 72 + off] = a;
        reinterpret_cast<uint4*>(g_h2 + ((size_t)i * N_ + n0) * 64)[off] = b;
      }
    }
  }
  PROF(1, wg, 16);
  wg_wait<0>();
  fence_regs(acc);
  PROF(1, wg, 10);
#pragma unroll
  for (int i = 0; i < 48; ++i) af[i] = pack_bf16(acc[2 * i], acc[2 * i + 1]);
  named_bar(1 + wg, 128);
#pragma unroll
  for (int i = 0; i < 12; ++i) {
    const int u = 2 * i + uh;
    stsm_x4(sHt + offH + (lvalid ? (uint32_t)((u >> 3) * 1152 + (((u ^ lph) & 7) << 4)) : 0u), af[4 * i], af[4 * i + 1], af[4 * i + 2], af[4 * i + 3]);
  }
  named_bar(1 + wg, 128);
#pragma unroll 4
  for (int it = 0; it < 12; ++it) {
    const int idx = it * 128 + t;
    if (idx < 1512) {
      const int i = idx / 72, off = idx - i * 72, tt = i / 3, ch = i - tt * 3;
      reinterpret_cast<uint4*>(g_q2 + ((size_t)i * N_ + n0) * 64)[off] = *reinterpret_cast<const uint4*>(pHt + tt * FS + ch * 1152 + off * 16);
    }
  }
  PROF(1, wg, 11);
}

constexpr int KB = 144;
constexpr int KCH = KB * 128;
constexpr int STAGE_BYTES = 3 * KCH;
constexpr int NSTAGE = 3;
constexpr int P2_Q_OFF = NSTAGE * STAGE_BYTES;
constexpr int P2_ML_OFF = P2_Q_OFF + 2 * TILE_BYTES;
constexpr int P2_BAR_OFF = P2_ML_OFF + 2048;
constexpr int P2_SMEM = P2_BAR_OFF + 128 + 1024;

constexpr int OPITCH = 400;
__device__ __forceinline__ uint32_t add_bf2(uint32_t a, uint32_t b) { return pack_bf16(bf_lo(a) + bf_lo(b), bf_hi(a) + bf_hi(b)); }

__global__ void __cluster_dims__(2, 1, 1) __launch_bounds__(384, 1) p2_kernel(__nv_bfloat16* __restrict__ out) {
  extern __shared__ uint8_t smem_raw[];
  const uint32_t sbase = (smem_u32(smem_raw) + 1023) & ~1023u;
  uint8_t* sptr = smem_raw + (sbase - smem_u32(smem_raw));
  const uint32_t sQ = sbase + P2_Q_OFF, sML = sbase + P2_ML_OFF, bars = sbase + P2_BAR_OFF;
  const uint32_t bFull = bars, bEmpty = bars + 24, bQFull = bars + 48, bQEmpty = bars + 64, bW = bars + 80, bXFree = bars + 88, bXFull = bars + 96;
  const int tid = threadIdx.x, lane = tid & 31;
  const int warp = __shfl_sync(0xffffffffu, tid >> 5, 0);
  const int cl = blockIdx.x >> 1, rank = blockIdx.x & 1;
  if (tid == 0) PROF(2, 3, 0);
  if (tid == 0) {
    for (int i = 0; i < NSTAGE; ++i) { mbar_init(bFull + 8 * i, 1); mbar_init(bEmpty + 8 * i, 8); }
    for (int i = 0; i < 2; ++i) { mbar_init(bQFull + 8 * i, 1); mbar_init(bQEmpty + 8 * i, 4); }
    mbar_init(bW, 1); mbar_init(bXFree, 8); mbar_init(bXFull, 1);
    mbar_expect_tx(bXFull, 13 * 128 * 16);
    fence_mbar_init();
  }
  const int f = cl / 9, c = cl - f * 9;
  const int nmain = 5 - rank;
  const int ntot = nmain + 1;
  const uint32_t sW0 = sbase + (ntot % NSTAGE) * STAGE_BYTES, sW1 = sW0 + WCH, sW2 = sbase + ((ntot + 1) % NSTAGE) * STAGE_BYTES;
  cluster_sync_all();
  pdl_wait();
  if (blockIdx.x == 0 && tid < 4) g_cnt[16 + tid] = 0;

  if (warp >= 8) {
    asm volatile("setmaxnreg.dec.sync.aligned.u32 40;");
    if (warp == 8 && lane == 0) {
      const __nv_bfloat16* kv = g_h2 + (size_t)(f * 3) * (N_ * 64);
#pragma unroll 1
      for (int i = 0; i < ntot; ++i) {
        const int blk = (i == 0) ? c : (rank * 5 + i - 1);
        const int st = i % NSTAGE;
        if (i >= NSTAGE) mbar_wait(bEmpty + 8 * st, ((i / NSTAGE) - 1) & 1);
        mbar_expect_tx(bFull + 8 * st, STAGE_BYTES);
#pragma unroll
        for (int ch = 0; ch < 3; ++ch) bulk_g2s(sbase + st * STAGE_BYTES + ch * KCH, kv + (size_t)ch * (N_ * 64) + (size_t)blk * KB * 64, KCH, bFull + 8 * st);
      }
      const __nv_bfloat16* wsrc = g_w + 3 * 3 * 192 * 64;
      mbar_expect_tx(bW, W_BYTES);
      mbar_wait(bEmpty + 8 * (ntot % NSTAGE), ((ntot / NSTAGE) - 1) & 1);
      bulk_g2s(sW0, wsrc, 2 * WCH, bW);
      mbar_wait(bEmpty + 8 * ((ntot + 1) % NSTAGE), (((ntot + 1) / NSTAGE) - 1) & 1);
      bulk_g2s(sW2, wsrc + 2 * 192 * 64, WCH, bW);
    } else if (warp == 9 && lane == 0) {
      const __nv_bfloat16* qsrc = g_q2 + (size_t)(f * 3) * (N_ * 64);
#pragma unroll 1
      for (int i = 0; i < 4; ++i) {
        const int sg = i >> 1, w = i & 1;
        const bool skip0 = (rank == 0 && w == 1);
        if (sg == 0 && skip0) continue;
        const int qr = sg ? (128 * c + 64 * w) : (rank ? 1152 + 64 * w : 1280);
        if (sg && !skip0) mbar_wait(bQEmpty + 8 * w, 0);
        mbar_expect_tx(bQFull + 8 * w, TILE_BYTES);
#pragma unroll
        for (int ch = 0; ch < 3; ++ch) bulk_g2s(sQ + w * TILE_BYTES + ch * 8192, qsrc + (size_t)ch * (N_ * 64) + (size_t)qr * 64, 8192, bQFull + 8 * w);
      }
    }
    return;
  }

  asm volatile("setmaxnreg.inc.sync.aligned.u32 232;");
  const int w = warp >> 2, wl = warp & 3, t = tid & 127;
  const int g = lane >> 2, q = lane & 3;
  const int r0 = wl * 16 + g;
  const uint32_t sQt = sQ + w * TILE_BYTES;
  PROF(2, w, 0);
  float o[96];
  float m0, m1, l0, l1;
  {
    const int nphase = nmain + 3;
    int phase = 0;
    if (w == 1) named_arrive(4, 256);
    auto acquire = [&]() { named_bar(4 + w, 256); };
    auto release = [&]() { ++phase; if (w == 0 || phase < nphase) named_arrive(4 + (w ^ 1), 256); };
    const bool skip0 = (rank == 0 && w == 1);
    int k = 0;
    unsigned int* pend = nullptr;
    const uint32_t dQ = make_desc(sQt, 16, 1024);
    if (skip0) {
      mbar_wait(bFull, 0);
      if (lane == 0) mbar_arrive(bEmpty);
      acquire(); release(); acquire(); release();
      k = 1;
    }
#pragma unroll 1
    for (int sg = skip0 ? 1 : 0; sg < 2; ++sg) {
      const int nblk = sg ? nmain : 1;
      mbar_wait(bQFull + 8 * w, skip0 ? 0 : sg);
      if (sg == 0) PROF(2, w, 1);
      m0 = m1 = -INFINITY; l0 = l1 = 0.f;
      uint32_t pf[36];
      uint32_t sK, bE;
      float sc[72];
      auto next_stage = [&]() {
        const int st = k % NSTAGE;
        sK = sbase + st * STAGE_BYTES; bE = bEmpty + 8 * st;
        mbar_wait(bFull + 8 * st, (k / NSTAGE) & 1);
        PROF(2, w, 2 + 3 * k);
      };
      auto issue_s = [&]() {
        const uint32_t dK = make_desc(sK, 16, 1024);
#pragma unroll
        for (int kk = 0; kk < 12; ++kk)
          wgmma_ss_n144<0, 0>(sc, dQ + ((kk >> 2) * 512 + (kk & 3) * 2), dK + ((kk >> 2) * (KCH / 16) + (kk & 3) * 2), kk > 0);
        wg_commit();
      };
      auto issue_pv = [&](uint32_t sV, int acc) {
        const uint32_t dV = make_desc(sV, KCH, 1024);
#pragma unroll
        for (int kk = 0; kk < 9; ++kk)
          wgmma_rs_n192<1>(o, pf[4 * kk], pf[4 * kk + 1], pf[4 * kk + 2], pf[4 * kk + 3], dV + kk * 128, acc || (kk > 0));
        wg_commit();
      };
      float a0, a1;
      auto softmax = [&](bool lastblk) {
        if (lastblk && lane == 0) {
          if (sg == 0) mbar_arrive(bQEmpty + 8 * w);
          else mbar_arrive_remote(mapa(bXFree, rank ^ 1));
        }
        float mx0 = sc[0], mx1 = sc[2];
#pragma unroll
        for (int j = 0; j < 18; ++j) {
          mx0 = fmaxf(mx0, fmaxf(sc[4 * j], sc[4 * j + 1]));
          mx1 = fmaxf(mx1, fmaxf(sc[4 * j + 2], sc[4 * j + 3]));
        }
        mx0 = fmaxf(mx0, __shfl_xor_sync(0xffffffffu, mx0, 1)); mx0 = fmaxf(mx0, __shfl_xor_sync(0xffffffffu, mx0, 2));
        mx1 = fmaxf(mx1, __shfl_xor_sync(0xffffffffu, mx1, 1)); mx1 = fmaxf(mx1, __shfl_xor_sync(0xffffffffu, mx1, 2));
        const float mn0 = fmaxf(m0, mx0), mn1 = fmaxf(m1, mx1);
        a0 = ex2((m0 - mn0) * SM_SCALE_LOG2); a1 = ex2((m1 - mn1) * SM_SCALE_LOG2);
        m0 = mn0; m1 = mn1;
        const float ms0 = mn0 * SM_SCALE_LOG2, ms1 = mn1 * SM_SCALE_LOG2;
        float ls0 = 0.f, ls1 = 0.f;
#pragma unroll
        for (int j = 0; j < 18; ++j) {
          sc[4 * j] = ex2(fmaf(sc[4 * j], SM_SCALE_LOG2, -ms0)); sc[4 * j + 1] = ex2(fmaf(sc[4 * j + 1], SM_SCALE_LOG2, -ms0));
          sc[4 * j + 2] = ex2(fmaf(sc[4 * j + 2], SM_SCALE_LOG2, -ms1)); sc[4 * j + 3] = ex2(fmaf(sc[4 * j + 3], SM_SCALE_LOG2, -ms1));
          ls0 += sc[4 * j] + sc[4 * j + 1]; ls1 += sc[4 * j + 2] + sc[4 * j + 3];
        }
        l0 = l0 * a0 + ls0; l1 = l1 * a1 + ls1;
      };
      next_stage();
      acquire();
      wg_fence();
      issue_s();
      release();
      wg_wait<0>();
      fence_regs(sc);
      PROF(2, w, 3 + 3 * k);
      softmax(nblk == 1);
#pragma unroll
      for (int j = 0; j < 36; ++j) pf[j] = pack_bf16(sc[2 * j], sc[2 * j + 1]);
      if (pend) {
        __threadfence();
        named_bar(1 + w, 128);
        if (t == 0) atomicAdd(pend, 1u);
      }
      ++k;
#pragma unroll 1
      for (int b = 1; b < nblk; ++b) {
        const uint32_t sV = sK, bEv = bE;
        next_stage();
        acquire();
        wg_fence();
        issue_s();
        issue_pv(sV, b > 1);
        release();
        wg_wait<1>();
        fence_regs(sc);
        PROF(2, w, 3 + 3 * k);
        softmax(b == nblk - 1);
        wg_wait<0>();
        fence_regs(o);
        if (lane == 0) mbar_arrive(bEv);
#pragma unroll
        for (int j = 0; j < 24; ++j) { o[4 * j] *= a0; o[4 * j + 1] *= a0; o[4 * j + 2] *= a1; o[4 * j + 3] *= a1; }
#pragma unroll
        for (int j = 0; j < 36; ++j) pf[j] = pack_bf16(sc[2 * j], sc[2 * j + 1]);
        ++k;
      }
      acquire();
      wg_fence();
      issue_pv(sK, nblk > 1);
      release();
      wg_wait<0>();
      fence_regs(o);
      if (lane == 0) mbar_arrive(bE);
      PROF(2, w, 1 + 3 * k);
      l0 += __shfl_xor_sync(0xffffffffu, l0, 1); l0 += __shfl_xor_sync(0xffffffffu, l0, 2);
      l1 += __shfl_xor_sync(0xffffffffu, l1, 1); l1 += __shfl_xor_sync(0xffffffffu, l1, 2);
      if (sg == 0) {
        const int slot = cl * 3 + (rank ? w : 2);
        if (rank || wl == 0) {
          uint4* po = g_part + (size_t)slot * (12 * 128) + t;
#pragma unroll
          for (int j = 0; j < 12; ++j)
            po[j * 128] = make_uint4(pack_bf16(o[8 * j], o[8 * j + 1]), pack_bf16(o[8 * j + 2], o[8 * j + 3]), pack_bf16(o[8 * j + 4], o[8 * j + 5]), pack_bf16(o[8 * j + 6], o[8 * j + 7]));
          g_pml[slot * 128 + t] = make_float4(m0, m1, l0, l1);
        }
        pend = g_cnt + f;
      }
    }
    PROF(2, w, 20);
    if (w != rank) {
      mbar_wait_cluster(bXFree, 0);
      const uint32_t rq = mapa(sQ, rank ^ 1) + t * 16, rb = mapa(bXFull, rank ^ 1);
#pragma unroll
      for (int i = 0; i < 12; ++i)
        st_async_v4(rq + i * 2048, __uint_as_float(pack_bf16(o[8 * i], o[8 * i + 1])), __uint_as_float(pack_bf16(o[8 * i + 2], o[8 * i + 3])),
                    __uint_as_float(pack_bf16(o[8 * i + 4], o[8 * i + 5])), __uint_as_float(pack_bf16(o[8 * i + 6], o[8 * i + 7])), rb);
      st_async_v4(mapa(sML, rank ^ 1) + t * 16, m0, m1, l0, l1, rb);
      PROF(2, w, 21);
      if (rank == 0) return;
    }
  }

  const bool recv = (w == rank);
  mbar_wait(bW, 0);
  const uint32_t sT = sW2 + WCH;
  const int grow = f * N_ + (recv ? (128 * c + 64 * w) : (1152 + 16 * c));
  uint32_t af[48];
  if (recv) {
    mbar_wait_cluster(bXFull, 0);
    PROF(2, w, 17);
    const float4 ml = *reinterpret_cast<const float4*>(sptr + P2_ML_OFF + t * 16);
    const float mn0 = fmaxf(m0, ml.x), mn1 = fmaxf(m1, ml.y);
    float a0 = ex2((m0 - mn0) * SM_SCALE_LOG2), a1 = ex2((m1 - mn1) * SM_SCALE_LOG2);
    float b0 = ex2((ml.x - mn0) * SM_SCALE_LOG2), b1 = ex2((ml.y - mn1) * SM_SCALE_LOG2);
    const float i0 = 1.f / (a0 * l0 + b0 * ml.z), i1 = 1.f / (a1 * l1 + b1 * ml.w);
    a0 *= i0; b0 *= i0; a1 *= i1; b1 *= i1;
#pragma unroll
    for (int i = 0; i < 12; ++i) {
      const uint4 v = *reinterpret_cast<const uint4*>(sptr + P2_Q_OFF + i * 2048 + t * 16);
      af[4 * i] = pack_bf16(a0 * o[8 * i] + b0 * bf_lo(v.x), a0 * o[8 * i + 1] + b0 * bf_hi(v.x));
      af[4 * i + 1] = pack_bf16(a1 * o[8 * i + 2] + b1 * bf_lo(v.y), a1 * o[8 * i + 3] + b1 * bf_hi(v.y));
      af[4 * i + 2] = pack_bf16(a0 * o[8 * i + 4] + b0 * bf_lo(v.z), a0 * o[8 * i + 5] + b0 * bf_hi(v.z));
      af[4 * i + 3] = pack_bf16(a1 * o[8 * i + 6] + b1 * bf_lo(v.w), a1 * o[8 * i + 7] + b1 * bf_hi(v.w));
    }
  } else {
    if (t == 0) wait_counter(g_cnt + f, 27);
    named_bar(1 + w, 128);
    __threadfence();
    const int slot0 = f * 27 + (c >> 2), tl = (c & 3) * 32 + lane;
    float4 mlv[9]; uint4 v[9][3];
#pragma unroll
    for (int i = 0; i < 9; ++i) {
      mlv[i] = __ldcg(g_pml + (slot0 + 3 * i) * 128 + tl);
#pragma unroll
      for (int j = 0; j < 3; ++j) v[i][j] = __ldcg(g_part + (size_t)(slot0 + 3 * i) * (12 * 128) + (wl * 3 + j) * 128 + tl);
    }
    float mn0 = mlv[0].x, mn1 = mlv[0].y;
#pragma unroll
    for (int i = 1; i < 9; ++i) { mn0 = fmaxf(mn0, mlv[i].x); mn1 = fmaxf(mn1, mlv[i].y); }
    float s0 = 0.f, s1 = 0.f;
#pragma unroll
    for (int i = 0; i < 9; ++i) {
      mlv[i].x = ex2((mlv[i].x - mn0) * SM_SCALE_LOG2); mlv[i].y = ex2((mlv[i].y - mn1) * SM_SCALE_LOG2);
      s0 += mlv[i].x * mlv[i].z; s1 += mlv[i].y * mlv[i].w;
    }
    s0 = 1.f / s0; s1 = 1.f / s1;
    uint8_t* pT = sptr + (sT - sbase);
#pragma unroll
    for (int j = 0; j < 3; ++j) {
      float x[8] = {};
#pragma unroll
      for (int i = 0; i < 9; ++i) {
        x[0] += mlv[i].x * bf_lo(v[i][j].x); x[1] += mlv[i].x * bf_hi(v[i][j].x); x[2] += mlv[i].y * bf_lo(v[i][j].y); x[3] += mlv[i].y * bf_hi(v[i][j].y);
        x[4] += mlv[i].x * bf_lo(v[i][j].z); x[5] += mlv[i].x * bf_hi(v[i][j].z); x[6] += mlv[i].y * bf_lo(v[i][j].w); x[7] += mlv[i].y * bf_hi(v[i][j].w);
      }
      const int col = (wl * 3 + j) * 16 + 2 * q;
      *reinterpret_cast<uint32_t*>(pT + g * OPITCH + col * 2) = pack_bf16(x[0] * s0, x[1] * s0);
      *reinterpret_cast<uint32_t*>(pT + (g + 8) * OPITCH + col * 2) = pack_bf16(x[2] * s1, x[3] * s1);
      *reinterpret_cast<uint32_t*>(pT + g * OPITCH + col * 2 + 16) = pack_bf16(x[4] * s0, x[5] * s0);
      *reinterpret_cast<uint32_t*>(pT + (g + 8) * OPITCH + col * 2 + 16) = pack_bf16(x[6] * s1, x[7] * s1);
    }
    named_bar(1 + w, 128);
#pragma unroll
    for (int j = 0; j < 24; ++j) {
      af[2 * j] = *reinterpret_cast<const uint32_t*>(pT + g * OPITCH + j * 16 + q * 4);
      af[2 * j + 1] = *reinterpret_cast<const uint32_t*>(pT + (g + 8) * OPITCH + j * 16 + q * 4);
    }
  }
  PROF(2, w, 18);
  gemm_rs_w(o, af, sW0, sW1, sW2);
  const int nit = recv ? 12 : 3;
  uint4 xv[12];
  {
    const uint4* src = reinterpret_cast<const uint4*>(g_x1 + (size_t)grow * C_) + t;
#pragma unroll
    for (int it = 0; it < 12; ++it) if (it < nit) xv[it] = __ldcg(src + it * 128);
  }
  named_bar(1 + w, 128);
  wg_wait<0>();
  fence_regs(o);
  PROF(2, w, 22);
  const uint32_t sS = recv ? sQ : sT;
  if (recv || wl == 0) {
    const uint32_t addr = sS + (wl * 16 + ((lane >> 3) & 1) * 8 + (lane & 7)) * OPITCH + (lane >> 4) * 16;
#pragma unroll
    for (int i = 0; i < 12; ++i)
      stsm_x4(addr + i * 32, pack_bf16(o[8 * i], o[8 * i + 1]), pack_bf16(o[8 * i + 2], o[8 * i + 3]),
              pack_bf16(o[8 * i + 4], o[8 * i + 5]), pack_bf16(o[8 * i + 6], o[8 * i + 7]));
  }
  named_bar(1 + w, 128);
  {
    const uint8_t* pS = sptr + (sS - sbase);
    uint4* dst = reinterpret_cast<uint4*>(out + (size_t)grow * C_);
#pragma unroll
    for (int it = 0; it < 12; ++it) {
      if (it < nit) {
        const int unit = it * 128 + t, row = unit / 24, u = unit - row * 24;
        const uint4 y = *reinterpret_cast<const uint4*>(pS + row * OPITCH + u * 16);
        dst[unit] = make_uint4(add_bf2(xv[it].x, y.x), add_bf2(xv[it].y, y.y), add_bf2(xv[it].z, y.z), add_bf2(xv[it].w, y.w));
      }
    }
  }
  PROF(2, w, 23);
}

}

extern "C" void kernel_launch(void* const* d_in, const int* in_sizes, int n_in, void* d_out, int out_size) {
  using namespace tsf;
  const __nv_bfloat16* x = (const __nv_bfloat16*)d_in[0];
  const __nv_bfloat16* wqkv_t = (const __nv_bfloat16*)d_in[1];
  const __nv_bfloat16* wo_t = (const __nv_bfloat16*)d_in[2];
  const __nv_bfloat16* wqkv_s = (const __nv_bfloat16*)d_in[3];
  const __nv_bfloat16* wo_s = (const __nv_bfloat16*)d_in[4];
  __nv_bfloat16* out = (__nv_bfloat16*)d_out;
  static bool init = false;
  if (!init) {
    cudaFuncSetAttribute(p1_kernel, cudaFuncAttributeMaxDynamicSharedMemorySize, P1_SMEM);
    cudaFuncSetAttribute(p2_kernel, cudaFuncAttributeMaxDynamicSharedMemorySize, P2_SMEM);
    cudaFuncSetAttribute(p1_kernel, cudaFuncAttributePreferredSharedMemoryCarveout, cudaSharedmemCarveoutMaxShared);
    cudaFuncSetAttribute(p2_kernel, cudaFuncAttributePreferredSharedMemoryCarveout, cudaSharedmemCarveoutMaxShared);
    init = true;
  }
  cudaStream_t st = cudaStreamPerThread;
  p1_kernel<<<132, 384, P1_SMEM, st>>>(x, wqkv_t, wo_t, wqkv_s, wo_s);
  cudaLaunchAttribute at[1];
  at[0].id = cudaLaunchAttributeProgrammaticStreamSerialization;
  at[0].val.programmaticStreamSerializationAllowed = 1;
  {
    cudaLaunchConfig_t cfg = {};
    cfg.gridDim = dim3(126); cfg.blockDim = dim3(384); cfg.dynamicSmemBytes = P2_SMEM; cfg.stream = st;
    cfg.attrs = at; cfg.numAttrs = 1;
    cudaLaunchKernelEx(&cfg, p2_kernel, out);
  }
}
```

```cpp
#include <cuda_runtime.h>
#include <cuda_bf16.h>
#include <stdint.h>

namespace tsf {

constexpr int T_ = 7, N_ = 1296, C_ = 192, ROWS = T_ * N_;
constexpr float SM_SCALE_LOG2 = 0.07216878364870322f * 1.4426950408889634f;
constexpr uint32_t SPIN_LIMIT = 1u << 24;

__device__ __align__(1024) __nv_bfloat16 g_w[4 * 3 * 192 * 64];
__device__ __align__(1024) __nv_bfloat16 g_x1[ROWS * C_];
__device__ __align__(1024) __nv_bfloat16 g_h2[T_ * 3 * N_ * 64];
__device__ __align__(1024) __nv_bfloat16 g_q2[T_ * 3 * N_ * 64 + 64 * 64];
__device__ __align__(1024) uint4 g_part[189 * 12 * 128];
__device__ float4 g_pml[189 * 128];
__device__ unsigned int g_cnt[24];

#define PROF(kern, slot, idx)
__device__ __forceinline__ uint32_t smem_u32(const void* p) { return (uint32_t)__cvta_generic_to_shared(p); }
__device__ __forceinline__ void mbar_init(uint32_t bar, uint32_t count) {
  asm volatile("mbarrier.init.shared::cta.b64 [%0], %1;" ::"r"(bar), "r"(count) : "memory");
}
__device__ __forceinline__ void mbar_expect_tx(uint32_t bar, uint32_t bytes) {
  asm volatile("mbarrier.arrive.expect_tx.shared::cta.b64 _, [%0], %1;" ::"r"(bar), "r"(bytes) : "memory");
}
__device__ __forceinline__ void mbar_arrive(uint32_t bar) {
  asm volatile("mbarrier.arrive.shared::cta.b64 _, [%0];" ::"r"(bar) : "memory");
}
__device__ __forceinline__ void mbar_arrive_remote(uint32_t rbar) {
  asm volatile("mbarrier.arrive.release.cluster.shared::cluster.b64 _, [%0];" ::"r"(rbar) : "memory");
}
__device__ __forceinline__ bool mbar_try(uint32_t bar, uint32_t parity) {
  uint32_t ok;
  asm volatile("{\n.reg .pred p;\nmbarrier.try_wait.parity.shared::cta.b64 p, [%1], %2;\nselp.u32 %0, 1, 0, p;\n}\n"
               : "=r"(ok) : "r"(bar), "r"(parity) : "memory");
  return ok != 0;
}
__device__ __forceinline__ bool mbar_try_cluster(uint32_t bar, uint32_t parity) {
  uint32_t ok;
  asm volatile("{\n.reg .pred p;\nmbarrier.try_wait.parity.acquire.cluster.shared::cta.b64 p, [%1], %2;\nselp.u32 %0, 1, 0, p;\n}\n"
               : "=r"(ok) : "r"(bar), "r"(parity) : "memory");
  return ok != 0;
}
__device__ __forceinline__ void mbar_wait(uint32_t bar, uint32_t parity) {
#pragma unroll 1
  for (uint32_t it = 0; it < SPIN_LIMIT; ++it)
    if (mbar_try(bar, parity)) return;
  __trap();
}
__device__ __forceinline__ void mbar_wait_cluster(uint32_t bar, uint32_t parity) {
#pragma unroll 1
  for (uint32_t it = 0; it < SPIN_LIMIT; ++it)
    if (mbar_try_cluster(bar, parity)) return;
  __trap();
}
__device__ __forceinline__ void bulk_g2s(uint32_t dst, const void* src, uint32_t bytes, uint32_t bar) {
  asm volatile("cp.async.bulk.shared::cluster.global.mbarrier::complete_tx::bytes [%0], [%1], %2, [%3];"
               ::"r"(dst), "l"(src), "r"(bytes), "r"(bar) : "memory");
}
__device__ __forceinline__ void fence_async_smem() { asm volatile("fence.proxy.async.shared::cta;" ::: "memory"); }
__device__ __forceinline__ void fence_mbar_init() { asm volatile("fence.mbarrier_init.release.cluster;" ::: "memory"); }
__device__ __forceinline__ void named_bar(int id, int n) { asm volatile("bar.sync %0, %1;" ::"r"(id), "r"(n) : "memory"); }
__device__ __forceinline__ void wg_fence() { asm volatile("wgmma.fence.sync.aligned;" ::: "memory"); }
__device__ __forceinline__ void wg_commit() { asm volatile("wgmma.commit_group.sync.aligned;" ::: "memory"); }
template <int N> __device__ __forceinline__ void wg_wait() { asm volatile("wgmma.wait_group.sync.aligned %0;" ::"n"(N) : "memory"); }
template <int N> __device__ __forceinline__ void fence_regs(float (&d)[N]) {
#pragma unroll
  for (int i = 0; i < N; ++i) asm volatile("" : "+f"(d[i])::"memory");
}
__device__ __forceinline__ void pdl_wait() { asm volatile("griddepcontrol.wait;" ::: "memory"); }
__device__ __forceinline__ void pdl_launch() { asm volatile("griddepcontrol.launch_dependents;" ::: "memory"); }
__device__ __forceinline__ uint32_t mapa(uint32_t addr, uint32_t rank) {
  uint32_t r;
  asm volatile("mapa.shared::cluster.u32 %0, %1, %2;" : "=r"(r) : "r"(addr), "r"(rank));
  return r;
}
__device__ __forceinline__ void cluster_sync_all() {
  asm volatile("barrier.cluster.arrive.release.aligned;\nbarrier.cluster.wait.acquire.aligned;" ::: "memory");
}
__device__ __forceinline__ void st_cluster_v4(uint32_t addr, float a, float b, float c, float d) {
  asm volatile("st.shared::cluster.v4.f32 [%0], {%1, %2, %3, %4};" ::"r"(addr), "f"(a), "f"(b), "f"(c), "f"(d) : "memory");
}
__device__ __forceinline__ void st_async_v4(uint32_t addr, float a, float b, float c, float d, uint32_t rbar) {
  asm volatile("st.async.weak.shared::cluster.mbarrier::complete_tx::bytes.v4.f32 [%0], {%1, %2, %3, %4}, [%5];"
               ::"r"(addr), "f"(a), "f"(b), "f"(c), "f"(d), "r"(rbar) : "memory");
}
__device__ __forceinline__ uint32_t make_desc(uint32_t addr, uint32_t lbo, uint32_t) {
  return ((addr & 0x3FFFF) >> 4) | ((lbo >> 4) << 16);
}
__device__ __forceinline__ uint32_t pack_bf16(float lo, float hi) {
  uint32_t r;
  asm("cvt.rn.bf16x2.f32 %0, %1, %2;" : "=r"(r) : "f"(hi), "f"(lo));
  return r;
}
__device__ __forceinline__ float bf_lo(uint32_t v) { return __uint_as_float(v << 16); }
__device__ __forceinline__ float bf_hi(uint32_t v) { return __uint_as_float(v & 0xffff0000u); }
__device__ __forceinline__ float ex2(float x) {
  float r;
  asm("ex2.approx.ftz.f32 %0, %1;" : "=f"(r) : "f"(x));
  return r;
}
__device__ __forceinline__ void stsm_x4(uint32_t addr, uint32_t r0, uint32_t r1, uint32_t r2, uint32_t r3) {
  asm volatile("stmatrix.sync.aligned.m8n8.x4.shared.b16 [%0], {%1, %2, %3, %4};" ::"r"(addr), "r"(r0), "r"(r1), "r"(r2), "r"(r3) : "memory");
}
__device__ __forceinline__ void bulk_s2g(void* dst, uint32_t src, uint32_t bytes) {
  asm volatile("cp.async.bulk.global.shared::cta.bulk_group [%0], [%1], %2;" ::"l"(dst), "r"(src), "r"(bytes) : "memory");
}
__device__ __forceinline__ void bulk_commit() { asm volatile("cp.async.bulk.commit_group;" ::: "memory"); }
__device__ __forceinline__ void bulk_wait_read() { asm volatile("cp.async.bulk.wait_group.read 0;" ::: "memory"); }
__device__ __forceinline__ void bulk_wait_all() { asm volatile("cp.async.bulk.wait_group 0;" ::: "memory"); }
__device__ __forceinline__ void named_arrive(int id, int n) { asm volatile("bar.arrive %0, %1;" ::"r"(id), "r"(n) : "memory"); }
__device__ __forceinline__ void wait_counter(const unsigned int* p, unsigned int target) {
#pragma unroll 1
  for (uint32_t it = 0; it < SPIN_LIMIT; ++it) {
    unsigned int v;
    asm volatile("ld.acquire.gpu.global.u32 %0, [%1];" : "=r"(v) : "l"(p) : "memory");
    if (v >= target) return;
    __nanosleep(32);
  }
  __trap();
}
__device__ __forceinline__ void fence_async_all() { asm volatile("fence.proxy.async;" ::: "memory"); }
__device__ __forceinline__ int swz(int row, int col) { return row * 64 + ((((col >> 3) ^ row) & 7) << 3) + (col & 7); }

template <int TA, int TB>
__device__ __forceinline__ void wgmma_ss_n48(float (&d)[24], uint32_t da, uint32_t db, int sc) {
  asm volatile("{\n.reg .pred p;\n.reg .b64 da, db;\n.reg .b32 hi;\nmov.b32 hi, 0x40000040;\nmov.b64 da, {%24, hi};\nmov.b64 db, {%25, hi};\nsetp.ne.b32 p, %26, 0;\n"
    "wgmma.mma_async.sync.aligned.m64n48k16.f32.bf16.bf16 "
    "{%0, %1, %2, %3, %4, %5, %6, %7, %8, %9, %10, %11, %12, %13, %14, %15, %16, %17, %18, %19, %20, %21, %22, %23}, "
    "da, db, p, 1, 1, %27, %28;\n}\n"
    : "+f"(d[0]), "+f"(d[1]), "+f"(d[2]), "+f"(d[3]), "+f"(d[4]), "+f"(d[5]), "+f"(d[6]), "+f"(d[7]), "+f"(d[8]), "+f"(d[9]), "+f"(d[10]), "+f"(d[11]), "+f"(d[12]), "+f"(d[13]), "+f"(d[14]), "+f"(d[15]), "+f"(d[16]), "+f"(d[17]), "+f"(d[18]), "+f"(d[19]), "+f"(d[20]), "+f"(d[21]), "+f"(d[22]), "+f"(d[23])
    : "r"(da), "r"(db), "r"(sc), "n"(TA), "n"(TB));
}
template <int TA, int TB>
__device__ __forceinline__ void wgmma_ss_n192(float (&d)[96], uint32_t da, uint32_t db, int sc) {
  asm volatile("{\n.reg .pred p;\n.reg .b64 da, db;\n.reg .b32 hi;\nmov.b32 hi, 0x40000040;\nmov.b64 da, {%96, hi};\nmov.b64 db, {%97, hi};\nsetp.ne.b32 p, %98, 0;\n"
    "wgmma.mma_async.sync.aligned.m64n192k16.f32.bf16.bf16 "
    "{%0, %1, %2, %3, %4, %5, %6, %7, %8, %9, %10, %11, %12, %13, %14, %15, %16, %17, %18, %19, %20, %21, %22, %23, %24, %25, %26, %27, %28, %29, %30, %31, %32, %33, %34, %35, %36, %37, %38, %39, %40, %41, %42, %43, %44, %45, %46, %47, %48, %49, %50, %51, %52, %53, %54, %55, %56, %57, %58, %59, %60, %61, %62, %63, %64, %65, %66, %67, %68, %69, %70, %71, %72, %73, %74, %75, %76, %77, %78, %79, %80, %81, %82, %83, %84, %85, %86, %87, %88, %89, %90, %91, %92, %93, %94, %95}, "
    "da, db, p, 1, 1, %99, %100;\n}\n"
    : "+f"(d[0]), "+f"(d[1]), "+f"(d[2]), "+f"(d[3]), "+f"(d[4]), "+f"(d[5]), "+f"(d[6]), "+f"(d[7]), "+f"(d[8]), "+f"(d[9]), "+f"(d[10]), "+f"(d[11]), "+f"(d[12]), "+f"(d[13]), "+f"(d[14]), "+f"(d[15]), "+f"(d[16]), "+f"(d[17]), "+f"(d[18]), "+f"(d[19]), "+f"(d[20]), "+f"(d[21]), "+f"(d[22]), "+f"(d[23]), "+f"(d[24]), "+f"(d[25]), "+f"(d[26]), "+f"(d[27]), "+f"(d[28]), "+f"(d[29]), "+f"(d[30]), "+f"(d[31]), "+f"(d[32]), "+f"(d[33]), "+f"(d[34]), "+f"(d[35]), "+f"(d[36]), "+f"(d[37]), "+f"(d[38]), "+f"(d[39]), "+f"(d[40]), "+f"(d[41]), "+f"(d[42]), "+f"(d[43]), "+f"(d[44]), "+f"(d[45]), "+f"(d[46]), "+f"(d[47]), "+f"(d[48]), "+f"(d[49]), "+f"(d[50]), "+f"(d[51]), "+f"(d[52]), "+f"(d[53]), "+f"(d[54]), "+f"(d[55]), "+f"(d[56]), "+f"(d[57]), "+f"(d[58]), "+f"(d[59]), "+f"(d[60]), "+f"(d[61]), "+f"(d[62]), "+f"(d[63]), "+f"(d[64]), "+f"(d[65]), "+f"(d[66]), "+f"(d[67]), "+f"(d[68]), "+f"(d[69]), "+f"(d[70]), "+f"(d[71]), "+f"(d[72]), "+f"(d[73]), "+f"(d[74]), "+f"(d[75]), "+f"(d[76]), "+f"(d[77]), "+f"(d[78]), "+f"(d[79]), "+f"(d[80]), "+f"(d[81]), "+f"(d[82]), "+f"(d[83]), "+f"(d[84]), "+f"(d[85]), "+f"(d[86]), "+f"(d[87]), "+f"(d[88]), "+f"(d[89]), "+f"(d[90]), "+f"(d[91]), "+f"(d[92]), "+f"(d[93]), "+f"(d[94]), "+f"(d[95])
    : "r"(da), "r"(db), "r"(sc), "n"(TA), "n"(TB));
}
template <int TB>
__device__ __forceinline__ void wgmma_rs_n192(float (&d)[96], uint32_t a0, uint32_t a1, uint32_t a2, uint32_t a3, uint32_t db, int sc) {
  asm volatile("{\n.reg .pred p;\n.reg .b64 db;\n.reg .b32 hi;\nmov.b32 hi, 0x40000040;\nmov.b64 db, {%100, hi};\nsetp.ne.b32 p, %101, 0;\n"
    "wgmma.mma_async.sync.aligned.m64n192k16.f32.bf16.bf16 "
    "{%0, %1, %2, %3, %4, %5, %6, %7, %8, %9, %10, %11, %12, %13, %14, %15, %16, %17, %18, %19, %20, %21, %22, %23, %24, %25, %26, %27, %28, %29, %30, %31, %32, %33, %34, %35, %36, %37, %38, %39, %40, %41, %42, %43, %44, %45, %46, %47, %48, %49, %50, %51, %52, %53, %54, %55, %56, %57, %58, %59, %60, %61, %62, %63, %64, %65, %66, %67, %68, %69, %70, %71, %72, %73, %74, %75, %76, %77, %78, %79, %80, %81, %82, %83, %84, %85, %86, %87, %88, %89, %90, %91, %92, %93, %94, %95}, "
    "{%96, %97, %98, %99}, db, p, 1, 1, %102;\n}\n"
    : "+f"(d[0]), "+f"(d[1]), "+f"(d[2]), "+f"(d[3]), "+f"(d[4]), "+f"(d[5]), "+f"(d[6]), "+f"(d[7]), "+f"(d[8]), "+f"(d[9]), "+f"(d[10]), "+f"(d[11]), "+f"(d[12]), "+f"(d[13]), "+f"(d[14]), "+f"(d[15]), "+f"(d[16]), "+f"(d[17]), "+f"(d[18]), "+f"(d[19]), "+f"(d[20]), "+f"(d[21]), "+f"(d[22]), "+f"(d[23]), "+f"(d[24]), "+f"(d[25]), "+f"(d[26]), "+f"(d[27]), "+f"(d[28]), "+f"(d[29]), "+f"(d[30]), "+f"(d[31]), "+f"(d[32]), "+f"(d[33]), "+f"(d[34]), "+f"(d[35]), "+f"(d[36]), "+f"(d[37]), "+f"(d[38]), "+f"(d[39]), "+f"(d[40]), "+f"(d[41]), "+f"(d[42]), "+f"(d[43]), "+f"(d[44]), "+f"(d[45]), "+f"(d[46]), "+f"(d[47]), "+f"(d[48]), "+f"(d[49]), "+f"(d[50]), "+f"(d[51]), "+f"(d[52]), "+f"(d[53]), "+f"(d[54]), "+f"(d[55]), "+f"(d[56]), "+f"(d[57]), "+f"(d[58]), "+f"(d[59]), "+f"(d[60]), "+f"(d[61]), "+f"(d[62]), "+f"(d[63]), "+f"(d[64]), "+f"(d[65]), "+f"(d[66]), "+f"(d[67]), "+f"(d[68]), "+f"(d[69]), "+f"(d[70]), "+f"(d[71]), "+f"(d[72]), "+f"(d[73]), "+f"(d[74]), "+f"(d[75]), "+f"(d[76]), "+f"(d[77]), "+f"(d[78]), "+f"(d[79]), "+f"(d[80]), "+f"(d[81]), "+f"(d[82]), "+f"(d[83]), "+f"(d[84]), "+f"(d[85]), "+f"(d[86]), "+f"(d[87]), "+f"(d[88]), "+f"(d[89]), "+f"(d[90]), "+f"(d[91]), "+f"(d[92]), "+f"(d[93]), "+f"(d[94]), "+f"(d[95])
    : "r"(a0), "r"(a1), "r"(a2), "r"(a3), "r"(db), "r"(sc), "n"(TB));
}
template <int TB>
__device__ __forceinline__ void wgmma_rs_n64(float (&d)[32], uint32_t a0, uint32_t a1, uint32_t a2, uint32_t a3, uint32_t db, int sc) {
  asm volatile("{\n.reg .pred p;\n.reg .b64 db;\n.reg .b32 hi;\nmov.b32 hi, 0x40000040;\nmov.b64 db, {%36, hi};\nsetp.ne.b32 p, %37, 0;\n"
    "wgmma.mma_async.sync.aligned.m64n64k16.f32.bf16.bf16 "
    "{%0, %1, %2, %3, %4, %5, %6, %7, %8, %9, %10, %11, %12, %13, %14, %15, %16, %17, %18, %19, %20, %21, %22, %23, %24, %25, %26, %27, %28, %29, %30, %31}, "
    "{%32, %33, %34, %35}, db, p, 1, 1, %38;\n}\n"
    : "+f"(d[0]), "+f"(d[1]), "+f"(d[2]), "+f"(d[3]), "+f"(d[4]), "+f"(d[5]), "+f"(d[6]), "+f"(d[7]), "+f"(d[8]), "+f"(d[9]), "+f"(d[10]), "+f"(d[11]), "+f"(d[12]), "+f"(d[13]), "+f"(d[14]), "+f"(d[15]), "+f"(d[16]), "+f"(d[17]), "+f"(d[18]), "+f"(d[19]), "+f"(d[20]), "+f"(d[21]), "+f"(d[22]), "+f"(d[23]), "+f"(d[24]), "+f"(d[25]), "+f"(d[26]), "+f"(d[27]), "+f"(d[28]), "+f"(d[29]), "+f"(d[30]), "+f"(d[31])
    : "r"(a0), "r"(a1), "r"(a2), "r"(a3), "r"(db), "r"(sc), "n"(TB));
}
template <int TA, int TB>
__device__ __forceinline__ void wgmma_ss_n144(float (&d)[72], uint32_t da, uint32_t db, int sc) {
  asm volatile("{\n.reg .pred p;\n.reg .b64 da, db;\n.reg .b32 hi;\nmov.b32 hi, 0x40000040;\nmov.b64 da, {%72, hi};\nmov.b64 db, {%73, hi};\nsetp.ne.b32 p, %74, 0;\n"
    "wgmma.mma_async.sync.aligned.m64n144k16.f32.bf16.bf16 "
    "{%0, %1, %2, %3, %4, %5, %6, %7, %8, %9, %10, %11, %12, %13, %14, %15, %16, %17, %18, %19, %20, %21, %22, %23, %24, %25, %26, %27, %28, %29, %30, %31, %32, %33, %34, %35, %36, %37, %38, %39, %40, %41, %42, %43, %44, %45, %46, %47, %48, %49, %50, %51, %52, %53, %54, %55, %56, %57, %58, %59, %60, %61, %62, %63, %64, %65, %66, %67, %68, %69, %70, %71}, "
    "da, db, p, 1, 1, %75, %76;\n}\n"
    : "+f"(d[0]), "+f"(d[1]), "+f"(d[2]), "+f"(d[3]), "+f"(d[4]), "+f"(d[5]), "+f"(d[6]), "+f"(d[7]), "+f"(d[8]), "+f"(d[9]), "+f"(d[10]), "+f"(d[11]), "+f"(d[12]), "+f"(d[13]), "+f"(d[14]), "+f"(d[15]), "+f"(d[16]), "+f"(d[17]), "+f"(d[18]), "+f"(d[19]), "+f"(d[20]), "+f"(d[21]), "+f"(d[22]), "+f"(d[23]), "+f"(d[24]), "+f"(d[25]), "+f"(d[26]), "+f"(d[27]), "+f"(d[28]), "+f"(d[29]), "+f"(d[30]), "+f"(d[31]), "+f"(d[32]), "+f"(d[33]), "+f"(d[34]), "+f"(d[35]), "+f"(d[36]), "+f"(d[37]), "+f"(d[38]), "+f"(d[39]), "+f"(d[40]), "+f"(d[41]), "+f"(d[42]), "+f"(d[43]), "+f"(d[44]), "+f"(d[45]), "+f"(d[46]), "+f"(d[47]), "+f"(d[48]), "+f"(d[49]), "+f"(d[50]), "+f"(d[51]), "+f"(d[52]), "+f"(d[53]), "+f"(d[54]), "+f"(d[55]), "+f"(d[56]), "+f"(d[57]), "+f"(d[58]), "+f"(d[59]), "+f"(d[60]), "+f"(d[61]), "+f"(d[62]), "+f"(d[63]), "+f"(d[64]), "+f"(d[65]), "+f"(d[66]), "+f"(d[67]), "+f"(d[68]), "+f"(d[69]), "+f"(d[70]), "+f"(d[71])
    : "r"(da), "r"(db), "r"(sc), "n"(TA), "n"(TB));
}

__device__ __forceinline__ void fuse_weights(uint32_t sbase, uint8_t* sptr, int j, const __nv_bfloat16* __restrict__ wqkv_t,
                                             const __nv_bfloat16* __restrict__ wo_t, const __nv_bfloat16* __restrict__ wqkv_s,
                                             const __nv_bfloat16* __restrict__ wo_s) {
  const int m = j / 12, n0 = ((j % 12) >> 2) * 64, k0 = (j & 3) * 48;
  const __nv_bfloat16* wqkv = (m < 2) ? wqkv_t : wqkv_s;
  const __nv_bfloat16* wo = (m < 2) ? wo_t : wo_s;
  const int tid = threadIdx.x;
  const bool odd = m & 1;
  uint8_t* pA = sptr; uint8_t* pB = sptr + 24576;
  uint4 va[4], vb[3];
#pragma unroll
  for (int i = 0; i < 4; ++i) {
    const int u = tid + i * 384;
    const int row = odd ? (u >> 3) : (u / 24), cu = odd ? (u & 7) : (u % 24);
    va[i] = __ldg(reinterpret_cast<const uint4*>(odd ? (wo + row * 192 + n0 + cu * 8) : (wqkv + (n0 + row) * 576 + 192 + cu * 8)));
  }
#pragma unroll
  for (int i = 0; i < 3; ++i) {
    const int u = tid + i * 384, row = u / 24, cu = u % 24;
    vb[i] = __ldg(reinterpret_cast<const uint4*>(wqkv + (k0 + row) * 576 + (odd ? 384 : 0) + cu * 8));
  }
#pragma unroll
  for (int i = 0; i < 4; ++i) {
    const int u = tid + i * 384;
    const int row = odd ? (u >> 3) : (u / 24), cu = odd ? (u & 7) : (u % 24);
    *reinterpret_cast<uint4*>(pA + (cu >> 3) * 8192 + row * 128 + (((cu ^ row) & 7) << 4)) = va[i];
  }
#pragma unroll
  for (int i = 0; i < 3; ++i) {
    const int u = tid + i * 384, row = u / 24, cu = u % 24;
    *reinterpret_cast<uint4*>(pB + (cu >> 3) * 6144 + row * 128 + (((cu ^ row) & 7) << 4)) = vb[i];
  }
  fence_async_smem();
  __syncthreads();
  if (tid < 128) {
    float acc[24];
    const uint32_t dB = make_desc(sbase + 24576, 16, 1024);
    wg_fence();
    if (odd) {
      const uint32_t dA = make_desc(sbase, 8192, 1024);
#pragma unroll
      for (int kk = 0; kk < 12; ++kk) wgmma_ss_n48<1, 0>(acc, dA + kk * 128, dB + ((kk >> 2) * 384 + (kk & 3) * 2), kk > 0);
    } else {
      const uint32_t dA = make_desc(sbase, 16, 1024);
#pragma unroll
      for (int kk = 0; kk < 12; ++kk) wgmma_ss_n48<0, 0>(acc, dA + ((kk >> 2) * 512 + (kk & 3) * 2), dB + ((kk >> 2) * 384 + (kk & 3) * 2), kk > 0);
    }
    wg_commit();
    wg_wait<0>();
    fence_regs(acc);
    const int lane = tid & 31, r0 = n0 + (tid >> 5) * 16 + (lane >> 2);
    __nv_bfloat16* dst = g_w + (size_t)m * 3 * 192 * 64;
#pragma unroll
    for (int jj = 0; jj < 6; ++jj) {
      const int k = k0 + 8 * jj + 2 * (lane & 3);
      __nv_bfloat16* ch = dst + (k >> 6) * (192 * 64);
      *reinterpret_cast<uint32_t*>(ch + swz(r0, k & 63)) = pack_bf16(acc[4 * jj], acc[4 * jj + 1]);
      *reinterpret_cast<uint32_t*>(ch + swz(r0 + 8, k & 63)) = pack_bf16(acc[4 * jj + 2], acc[4 * jj + 3]);
    }
    __threadfence();
    named_bar(1, 128);
    if (tid == 0) atomicAdd(g_cnt + 16 + m, 1u);
  }
}

constexpr int W_BYTES = 3 * 192 * 128;
constexpr int WCH = 192 * 128;
constexpr int TILE_BYTES = 3 * 64 * 128;
constexpr int P1_SMEM = 2 * W_BYTES + 2 * TILE_BYTES + 128 + 1024;
constexpr int FS = 3472;

__device__ __forceinline__ void gemm_rs_w(float (&acc)[96], const uint32_t (&a)[48], uint32_t c0, uint32_t c1, uint32_t c2) {
  wg_fence();
#pragma unroll
  for (int kk = 0; kk < 12; ++kk) {
    const uint32_t base = (kk < 4) ? c0 : ((kk < 8) ? c1 : c2);
    wgmma_rs_n192<0>(acc, a[4 * kk], a[4 * kk + 1], a[4 * kk + 2], a[4 * kk + 3], make_desc(base + (kk & 3) * 32, 16, 1024), kk > 0);
  }
  wg_commit();
}
__device__ __forceinline__ void gemm_ss_w(float (&acc)[96], uint32_t atile, uint32_t c0, uint32_t c1, uint32_t c2) {
  wg_fence();
#pragma unroll
  for (int kk = 0; kk < 12; ++kk) {
    const uint32_t base = (kk < 4) ? c0 : ((kk < 8) ? c1 : c2);
    wgmma_ss_n192<0, 0>(acc, make_desc(atile + (kk >> 2) * 8192 + (kk & 3) * 32, 16, 1024), make_desc(base + (kk & 3) * 32, 16, 1024), kk > 0);
  }
  wg_commit();
}

__global__ void __launch_bounds__(384, 1) p1_kernel(const __nv_bfloat16* __restrict__ x, const __nv_bfloat16* __restrict__ wqkv_t,
                                                    const __nv_bfloat16* __restrict__ wo_t, const __nv_bfloat16* __restrict__ wqkv_s,
                                                    const __nv_bfloat16* __restrict__ wo_s) {
  extern __shared__ uint8_t smem_raw[];
  const uint32_t sbase = (smem_u32(smem_raw) + 1023) & ~1023u;
  uint8_t* sptr = smem_raw + (sbase - smem_u32(smem_raw));
  if (blockIdx.x < 48) {
    PROF(0, 0, 0);
    pdl_launch();
    if (blockIdx.x == 0 && threadIdx.x >= 256 && threadIdx.x < 272) g_cnt[threadIdx.x - 256] = 0;
    fuse_weights(sbase, sptr, blockIdx.x, wqkv_t, wo_t, wqkv_s, wo_s);
    PROF(0, 0, 1);
    return;
  }
  const int bid = blockIdx.x - 48;
  const uint32_t sWA = sbase, sWB = sbase + W_BYTES, sH = sbase + 2 * W_BYTES;
  const uint32_t bars = sH + 2 * TILE_BYTES;
  const int tid = threadIdx.x, warp = tid >> 5, lane = tid & 31;
  if (tid == 0) PROF(1, 3, 0);
  pdl_launch();
  if (tid == 0) {
    mbar_init(bars, 1); mbar_init(bars + 8, 1); mbar_init(bars + 16, 1); mbar_init(bars + 24, 8); mbar_init(bars + 32, 4); mbar_init(bars + 40, 4);
    mbar_init(bars + 48, 1); mbar_init(bars + 56, 1); mbar_init(bars + 64, 8); mbar_init(bars + 72, 1); mbar_init(bars + 80, 1);
    fence_mbar_init();
  }
  __syncthreads();

  if (warp >= 8) {
    asm volatile("setmaxnreg.dec.sync.aligned.u32 40;");
    if (warp == 8 && lane == 0) {
#pragma unroll 1
      for (int i = 0; i < 14; ++i) {
        const int wg = i / 7, tt = i - wg * 7;
        if (tt == 0) mbar_expect_tx(bars + 48 + 8 * wg, 7 * 3456);
        bulk_g2s(sWB + wg * TILE_BYTES + tt * FS, x + ((size_t)tt * N_ + (bid * 2 + wg) * 9) * C_, 3456, bars + 48 + 8 * wg);
      }
      wait_counter(g_cnt + 16, 12);
      fence_async_all();
      mbar_expect_tx(bars, WCH);
      bulk_g2s(sWA, g_w, WCH, bars);
      mbar_expect_tx(bars + 72, WCH);
      bulk_g2s(sWA + WCH, g_w + 192 * 64, WCH, bars + 72);
      mbar_expect_tx(bars + 80, WCH);
      bulk_g2s(sWA + 2 * WCH, g_w + 2 * 192 * 64, WCH, bars + 80);
      wait_counter(g_cnt + 17, 12);
      fence_async_all();
      mbar_wait(bars + 64, 0);
      mbar_expect_tx(bars + 8, W_BYTES);
      bulk_g2s(sWB, g_w + 3 * 192 * 64, W_BYTES, bars + 8);
      wait_counter(g_cnt + 18, 12);
      fence_async_all();
      mbar_wait(bars + 24, 0);
      mbar_expect_tx(bars + 16, W_BYTES);
      bulk_g2s(sWA, g_w + 2 * 3 * 192 * 64, W_BYTES, bars + 16);
    }
    __syncwarp();
    named_bar(6, 384);
    {
      const int ht = tid - 256;
#pragma unroll 2
      for (int it = 0; it < 24; ++it) {
        const int wg = it >= 12, idx = (it - 12 * wg) * 128 + ht;
        if (idx < 1512) {
          const int n0 = (bid * 2 + wg) * 9;
          const int i = idx / 72, off = idx - i * 72, tt = i / 3, ch = i - tt * 3;
          const int so = wg * TILE_BYTES + tt * FS + ch * 1152 + off * 16;
          const uint4 a = *reinterpret_cast<const uint4*>(sptr + 2 * W_BYTES + so), b = *reinterpret_cast<const uint4*>(sptr + W_BYTES + so);
          reinterpret_cast<uint4*>(g_h2 + ((size_t)i * N_ + n0) * 64)[off] = b;
          reinterpret_cast<uint4*>(g_x1 + ((size_t)tt * N_ + n0) * C_)[ch * 72 + off] = a;
        }
      }
    }
    return;
  }

  asm volatile("setmaxnreg.inc.sync.aligned.u32 232;");
  const int wg = warp >> 2, t = tid & 127, wl = warp & 3;
  const int n0 = (bid * 2 + wg) * 9;
  const uint32_t sHt = sH + wg * TILE_BYTES;
  PROF(1, wg, 0);
  uint8_t* pHt = sptr + 2 * W_BYTES + wg * TILE_BYTES;
  {
    const uint8_t* pX = sptr + W_BYTES + wg * TILE_BYTES;
    const int l8 = lane & 7;
    mbar_wait(bars + 48 + 8 * wg, 0);
    uint4 v[4][3];
#pragma unroll
    for (int it = 0; it < 4; ++it) {
      const int row = wl * 16 + it * 4 + (lane >> 3);
      const int j = row / 7, tt = row - j * 7;
#pragma unroll
      for (int c = 0; c < 3; ++c)
        v[it][c] = (row < 63) ? *reinterpret_cast<const uint4*>(pX + tt * FS + j * 384 + (l8 + 8 * c) * 16) : make_uint4(0, 0, 0, 0);
    }
    __syncwarp();
    if (lane == 0) mbar_arrive(bars + 64);
#pragma unroll
    for (int it = 0; it < 4; ++it) {
      const int row = wl * 16 + it * 4 + (lane >> 3);
      float f[24];
#pragma unroll
      for (int c = 0; c < 3; ++c) {
        f[8 * c] = bf_lo(v[it][c].x); f[8 * c + 1] = bf_hi(v[it][c].x); f[8 * c + 2] = bf_lo(v[it][c].y); f[8 * c + 3] = bf_hi(v[it][c].y);
        f[8 * c + 4] = bf_lo(v[it][c].z); f[8 * c + 5] = bf_hi(v[it][c].z); f[8 * c + 6] = bf_lo(v[it][c].w); f[8 * c + 7] = bf_hi(v[it][c].w);
      }
      float s = 0.f;
#pragma unroll
      for (int e = 0; e < 24; ++e) s += f[e];
      s += __shfl_xor_sync(0xffffffffu, s, 1); s += __shfl_xor_sync(0xffffffffu, s, 2); s += __shfl_xor_sync(0xffffffffu, s, 4);
      const float mean = s * (1.f / 192.f);
      float ss = 0.f;
#pragma unroll
      for (int e = 0; e < 24; ++e) { f[e] -= mean; ss += f[e] * f[e]; }
      ss += __shfl_xor_sync(0xffffffffu, ss, 1); ss += __shfl_xor_sync(0xffffffffu, ss, 2); ss += __shfl_xor_sync(0xffffffffu, ss, 4);
      const float rstd = 1.f / sqrtf(ss * (1.f / 192.f) + 1e-5f);
#pragma unroll
      for (int c = 0; c < 3; ++c)
        *reinterpret_cast<uint4*>(pHt + c * 8192 + row * 128 + (((l8 ^ row) & 7) << 4)) =
            make_uint4(pack_bf16(f[8 * c] * rstd, f[8 * c + 1] * rstd), pack_bf16(f[8 * c + 2] * rstd, f[8 * c + 3] * rstd),
                       pack_bf16(f[8 * c + 4] * rstd, f[8 * c + 5] * rstd), pack_bf16(f[8 * c + 6] * rstd, f[8 * c + 7] * rstd));
    }
  }
  PROF(1, wg, 1);
  fence_async_smem();
  named_bar(1 + wg, 128);

  const int g = lane >> 2, q = lane & 3;
  const int r0 = wl * 16 + g, r1 = r0 + 8;
  float acc[96];
  uint32_t af[48];
  mbar_wait(bars, 0);
  PROF(1, wg, 2);
  wg_fence();
#pragma unroll
  for (int kk = 0; kk < 12; ++kk) {
    if (kk == 4) mbar_wait(bars + 72, 0);
    if (kk == 8) mbar_wait(bars + 80, 0);
    wgmma_ss_n192<0, 0>(acc, make_desc(sHt + (kk >> 2) * 8192 + (kk & 3) * 32, 16, 1024), make_desc(sWA + (kk >> 2) * WCH + (kk & 3) * 32, 16, 1024), kk > 0);
  }
  wg_commit();
  wg_wait<0>();
  fence_regs(acc);
  PROF(1, wg, 3);
  if (lane == 0) mbar_arrive(bars + 24);
#pragma unroll
  for (int i = 0; i < 48; ++i) af[i] = pack_bf16(acc[2 * i], acc[2 * i + 1]);
  float sc[32];
  wg_fence();
#pragma unroll
  for (int kk = 0; kk < 12; ++kk)
    wgmma_rs_n64<0>(sc, af[4 * kk], af[4 * kk + 1], af[4 * kk + 2], af[4 * kk + 3],
                    make_desc(sHt + (kk >> 2) * 8192 + (kk & 3) * 32, 16, 1024), kk > 0);
  wg_commit();
  wg_wait<0>();
  fence_regs(sc);
  PROF(1, wg, 4);
  uint32_t pf[16];
  {
    const int g0 = r0 / 7, g1 = r1 / 7;
    float mx0 = -INFINITY, mx1 = -INFINITY;
#pragma unroll
    for (int j = 0; j < 8; ++j) {
#pragma unroll
      for (int e = 0; e < 2; ++e) {
        const int col = 8 * j + 2 * q + e;
        const int cg = col / 7;
        if (cg != g0) sc[4 * j + e] = -INFINITY;
        if (cg != g1) sc[4 * j + 2 + e] = -INFINITY;
        mx0 = fmaxf(mx0, sc[4 * j + e]);
        mx1 = fmaxf(mx1, sc[4 * j + 2 + e]);
      }
    }
    mx0 = fmaxf(mx0, __shfl_xor_sync(0xffffffffu, mx0, 1)); mx0 = fmaxf(mx0, __shfl_xor_sync(0xffffffffu, mx0, 2));
    mx1 = fmaxf(mx1, __shfl_xor_sync(0xffffffffu, mx1, 1)); mx1 = fmaxf(mx1, __shfl_xor_sync(0xffffffffu, mx1, 2));
    float l0 = 0.f, l1 = 0.f;
#pragma unroll
    for (int j = 0; j < 8; ++j) {
#pragma unroll
      for (int e = 0; e < 2; ++e) {
        sc[4 * j + e] = ex2((sc[4 * j + e] - mx0) * SM_SCALE_LOG2);
        sc[4 * j + 2 + e] = ex2((sc[4 * j + 2 + e] - mx1) * SM_SCALE_LOG2);
        l0 += sc[4 * j + e];
        l1 += sc[4 * j + 2 + e];
      }
    }
    l0 += __shfl_xor_sync(0xffffffffu, l0, 1); l0 += __shfl_xor_sync(0xffffffffu, l0, 2);
    l1 += __shfl_xor_sync(0xffffffffu, l1, 1); l1 += __shfl_xor_sync(0xffffffffu, l1, 2);
    const float i0 = 1.f / l0, i1 = 1.f / l1;
#pragma unroll
    for (int j = 0; j < 8; ++j) {
      pf[2 * j] = pack_bf16(sc[4 * j] * i0, sc[4 * j + 1] * i0);
      pf[2 * j + 1] = pack_bf16(sc[4 * j + 2] * i1, sc[4 * j + 3] * i1);
    }
  }
  wg_fence();
#pragma unroll
  for (int kk = 0; kk < 4; ++kk)
    wgmma_rs_n192<1>(acc, pf[4 * kk], pf[4 * kk + 1], pf[4 * kk + 2], pf[4 * kk + 3], make_desc(sHt + kk * 2048, 8192, 1024), kk > 0);
  wg_commit();
  wg_wait<0>();
  fence_regs(acc);
#pragma unroll
  for (int i = 0; i < 48; ++i) af[i] = pack_bf16(acc[2 * i], acc[2 * i + 1]);
  PROF(1, wg, 5);
  named_bar(1 + wg, 128);
  if (lane == 0) {
    mbar_expect_tx(bars + 32 + 8 * wg, (wl == 3 ? 1 : 2) * 3456);
#pragma unroll 1
    for (int tt = wl; tt < 7; tt += 4) bulk_g2s(sHt + tt * FS, x + ((size_t)tt * N_ + n0) * C_, 3456, bars + 32 + 8 * wg);
  }
  mbar_wait(bars + 8, 0);
  PROF(1, wg, 6);
  gemm_rs_w(acc, af, sWB, sWB + WCH, sWB + 2 * WCH);
  uint32_t xr[48];
  {
    const int j0 = r0 / 7, t0 = r0 - j0 * 7, j1 = min(r1, 62) / 7, t1 = min(r1, 62) - j1 * 7;
    const uint8_t* p0 = pHt + t0 * FS + j0 * 384 + q * 4;
    const uint8_t* p1 = pHt + t1 * FS + j1 * 384 + q * 4;
    mbar_wait(bars + 32 + 8 * wg, 0);
#pragma unroll
    for (int j = 0; j < 24; ++j) { xr[2 * j] = *reinterpret_cast<const uint32_t*>(p0 + 16 * j); xr[2 * j + 1] = *reinterpret_cast<const uint32_t*>(p1 + 16 * j); }
  }
  wg_wait<0>();
  fence_regs(acc);
  PROF(1, wg, 7);
  {
    float s0 = 0.f, s1 = 0.f;
#pragma unroll
    for (int j = 0; j < 24; ++j) {
      const uint32_t a = pack_bf16(bf_lo(xr[2 * j]) + acc[4 * j], bf_hi(xr[2 * j]) + acc[4 * j + 1]);
      const uint32_t b = pack_bf16(bf_lo(xr[2 * j + 1]) + acc[4 * j + 2], bf_hi(xr[2 * j + 1]) + acc[4 * j + 3]);
      xr[2 * j] = a; xr[2 * j + 1] = b;
      acc[4 * j] = bf_lo(a); acc[4 * j + 1] = bf_hi(a); acc[4 * j + 2] = bf_lo(b); acc[4 * j + 3] = bf_hi(b);
      s0 += acc[4 * j] + acc[4 * j + 1];
      s1 += acc[4 * j + 2] + acc[4 * j + 3];
    }
    s0 += __shfl_xor_sync(0xffffffffu, s0, 1); s0 += __shfl_xor_sync(0xffffffffu, s0, 2);
    s1 += __shfl_xor_sync(0xffffffffu, s1, 1); s1 += __shfl_xor_sync(0xffffffffu, s1, 2);
    const float mean0 = s0 * (1.f / 192.f), mean1 = s1 * (1.f / 192.f);
    float q0 = 0.f, q1 = 0.f;
#pragma unroll
    for (int j = 0; j < 24; ++j) {
      acc[4 * j] -= mean0; acc[4 * j + 1] -= mean0; acc[4 * j + 2] -= mean1; acc[4 * j + 3] -= mean1;
      q0 += acc[4 * j] * acc[4 * j] + acc[4 * j + 1] * acc[4 * j + 1];
      q1 += acc[4 * j + 2] * acc[4 * j + 2] + acc[4 * j + 3] * acc[4 * j + 3];
    }
    q0 += __shfl_xor_sync(0xffffffffu, q0, 1); q0 += __shfl_xor_sync(0xffffffffu, q0, 2);
    q1 += __shfl_xor_sync(0xffffffffu, q1, 1); q1 += __shfl_xor_sync(0xffffffffu, q1, 2);
    const float rs0 = 1.f / sqrtf(q0 * (1.f / 192.f) + 1e-5f), rs1 = 1.f / sqrtf(q1 * (1.f / 192.f) + 1e-5f);
#pragma unroll
    for (int j = 0; j < 24; ++j) {
      af[2 * j] = pack_bf16(acc[4 * j] * rs0, acc[4 * j + 1] * rs0);
      af[2 * j + 1] = pack_bf16(acc[4 * j + 2] * rs1, acc[4 * j + 3] * rs1);
    }
  }
  PROF(1, wg, 8);
  const int lrow = wl * 16 + ((lane >> 3) & 1) * 8 + (lane & 7), uh = lane >> 4;
  const int lj = lrow / 7, lt = lrow - lj * 7;
  const bool lvalid = lrow < 63;
  const uint32_t offX = lvalid ? (uint32_t)(lt * FS + lj * 384 + uh * 16) : 3456u;
  const uint32_t offH = lvalid ? (uint32_t)(lt * FS + lj * 128) : 3456u;
  const int lph = (n0 + lj) & 7;
  const uint32_t sStH = sWB + wg * TILE_BYTES;
  PROF(1, wg, 12);
  named_bar(3, 256);
  PROF(1, wg, 13);
#pragma unroll
  for (int i = 0; i < 12; ++i) {
    stsm_x4(sHt + offX + (lvalid ? i * 32 : 0), xr[4 * i], xr[4 * i + 1], xr[4 * i + 2], xr[4 * i + 3]);
    const int u = 2 * i + uh;
    stsm_x4(sStH + offH + (lvalid ? (uint32_t)((u >> 3) * 1152 + (((u ^ lph) & 7) << 4)) : 0u), af[4 * i], af[4 * i + 1], af[4 * i + 2], af[4 * i + 3]);
  }
  PROF(1, wg, 14);
  named_arrive(6, 384);
  mbar_wait(bars + 16, 0);
  PROF(1, wg, 9);
  gemm_rs_w(acc, af, sWA, sWA + WCH, sWA + 2 * WCH);
  PROF(1, wg, 16);
  wg_wait<0>();
  fence_regs(acc);
  PROF(1, wg, 10);
#pragma unroll
  for (int i = 0; i < 48; ++i) af[i] = pack_bf16(acc[2 * i], acc[2 * i + 1]);
  named_bar(3, 256);
#pragma unroll
  for (int i = 0; i < 12; ++i) {
    const int u = 2 * i + uh;
    stsm_x4(sWA + wg * TILE_BYTES + offH + (lvalid ? (uint32_t)((u >> 3) * 1152 + (((u ^ lph) & 7) << 4)) : 0u), af[4 * i], af[4 * i + 1], af[4 * i + 2], af[4 * i + 3]);
  }
  named_bar(1 + wg, 128);
#pragma unroll 4
  for (int it = 0; it < 12; ++it) {
    const int idx = it * 128 + t;
    if (idx < 1512) {
      const int i = idx / 72, off = idx - i * 72, tt = i / 3, ch = i - tt * 3;
      reinterpret_cast<uint4*>(g_q2 + ((size_t)i * N_ + n0) * 64)[off] = *reinterpret_cast<const uint4*>(sptr + wg * TILE_BYTES + tt * FS + ch * 1152 + off * 16);
    }
  }
  PROF(1, wg, 11);
}

constexpr int KB = 144;
constexpr int KCH = KB * 128;
constexpr int STAGE_BYTES = 3 * KCH;
constexpr int NSTAGE = 3;
constexpr int P2_Q_OFF = NSTAGE * STAGE_BYTES;
constexpr int P2_ML_OFF = P2_Q_OFF + 2 * TILE_BYTES;
constexpr int P2_BAR_OFF = P2_ML_OFF + 2048;
constexpr int P2_SMEM = P2_BAR_OFF + 128 + 1024;

constexpr int OPITCH = 400;
__device__ __forceinline__ uint32_t add_bf2(uint32_t a, uint32_t b) { return pack_bf16(bf_lo(a) + bf_lo(b), bf_hi(a) + bf_hi(b)); }

__global__ void __cluster_dims__(2, 1, 1) __launch_bounds__(384, 1) p2_kernel(__nv_bfloat16* __restrict__ out) {
  extern __shared__ uint8_t smem_raw[];
  const uint32_t sbase = (smem_u32(smem_raw) + 1023) & ~1023u;
  uint8_t* sptr = smem_raw + (sbase - smem_u32(smem_raw));
  const uint32_t sQ = sbase + P2_Q_OFF, sML = sbase + P2_ML_OFF, bars = sbase + P2_BAR_OFF;
  const uint32_t bFull = bars, bEmpty = bars + 24, bQ0 = bars + 48, bQ1 = bars + 64, bW = bars + 80, bXFree = bars + 88, bXFull = bars + 96, bQ0Free = bars + 104;
  const int tid = threadIdx.x, lane = tid & 31;
  const int warp = __shfl_sync(0xffffffffu, tid >> 5, 0);
  const int cl = blockIdx.x >> 1, rank = blockIdx.x & 1;
  if (tid == 0) PROF(2, 3, 0);
  if (tid == 0) {
    for (int i = 0; i < NSTAGE; ++i) { mbar_init(bFull + 8 * i, 1); mbar_init(bEmpty + 8 * i, 8); }
    for (int i = 0; i < 2; ++i) { mbar_init(bQ0 + 8 * i, 1); mbar_init(bQ1 + 8 * i, 1); }
    mbar_init(bQ0Free, rank ? 8 : 4);
    mbar_init(bW, 1); mbar_init(bXFree, 8); mbar_init(bXFull, 1);
    mbar_expect_tx(bXFull, 13 * 128 * 16);
    fence_mbar_init();
  }
  const int f = cl / 9, c = cl - f * 9;
  const int nmain = 5 - rank;
  const int ntot = nmain + 1;
  const uint32_t sW0 = sbase + (ntot % NSTAGE) * STAGE_BYTES, sW1 = sW0 + WCH, sW2 = sbase + ((ntot + 1) % NSTAGE) * STAGE_BYTES;
  cluster_sync_all();
  pdl_wait();
  if (blockIdx.x == 0 && tid < 4) g_cnt[16 + tid] = 0;

  if (warp >= 8) {
    asm volatile("setmaxnreg.dec.sync.aligned.u32 40;");
    if (warp == 8 && lane == 0) {
      const __nv_bfloat16* kv = g_h2 + (size_t)(f * 3) * (N_ * 64);
#pragma unroll 1
      for (int i = 0; i < ntot; ++i) {
        const int blk = (i == 0) ? c : (rank * 5 + i - 1);
        const int st = i % NSTAGE;
        if (i >= NSTAGE) mbar_wait(bEmpty + 8 * st, ((i / NSTAGE) - 1) & 1);
        if (i == 2) mbar_wait(bQ0Free, 0);
        mbar_expect_tx(bFull + 8 * st, STAGE_BYTES);
#pragma unroll
        for (int ch = 0; ch < 3; ++ch) bulk_g2s(sbase + st * STAGE_BYTES + ch * KCH, kv + (size_t)ch * (N_ * 64) + (size_t)blk * KB * 64, KCH, bFull + 8 * st);
      }
      const __nv_bfloat16* wsrc = g_w + 3 * 3 * 192 * 64;
      mbar_expect_tx(bW, W_BYTES);
      mbar_wait(bEmpty + 8 * (ntot % NSTAGE), ((ntot / NSTAGE) - 1) & 1);
      bulk_g2s(sW0, wsrc, 2 * WCH, bW);
      mbar_wait(bEmpty + 8 * ((ntot + 1) % NSTAGE), (((ntot + 1) / NSTAGE) - 1) & 1);
      bulk_g2s(sW2, wsrc + 2 * 192 * 64, WCH, bW);
    } else if (warp == 9 && lane == 0) {
      const __nv_bfloat16* qsrc = g_q2 + (size_t)(f * 3) * (N_ * 64);
#pragma unroll 1
      for (int i = 0; i < 4; ++i) {
        const int sg = i >> 1, w = i & 1;
        if (sg == 0 && rank == 0 && w == 1) continue;
        if (i == 2) mbar_wait(bFull, 0);
        const int qr = sg ? (128 * c + 64 * w) : (rank ? 1152 + 64 * w : 1280);
        const uint32_t bar = (sg ? bQ1 : bQ0) + 8 * w, dst = (sg ? sQ : sbase + 2 * STAGE_BYTES) + w * TILE_BYTES;
        mbar_expect_tx(bar, TILE_BYTES);
#pragma unroll
        for (int ch = 0; ch < 3; ++ch) bulk_g2s(dst + ch * 8192, qsrc + (size_t)ch * (N_ * 64) + (size_t)qr * 64, 8192, bar);
      }
    }
    if (warp >= 10 && (rank || warp == 10)) {
      named_bar(6 + warp - 10, 160);
      if (lane == 0) { __threadfence(); atomicAdd(g_cnt + f, 1u); }
    }
    return;
  }

  asm volatile("setmaxnreg.inc.sync.aligned.u32 232;");
  const int w = warp >> 2, wl = warp & 3, t = tid & 127;
  const int g = lane >> 2, q = lane & 3;
  const int r0 = wl * 16 + g;
  const uint32_t sQt = sQ + w * TILE_BYTES;
  PROF(2, w, 0);
  float o[96];
  float m0, m1, l0, l1;
  {
    const int nrel = w ? ntot : (ntot + rank);
    int phase = 0;
    if (w == 1) named_arrive(4, 256);
    auto acquire = [&]() { named_bar(4 + w, 256); };
    auto release = [&]() { ++phase; if (phase <= nrel) named_arrive(4 + (w ^ 1), 256); };
    const bool skip0 = (rank == 0 && w == 1);
    int k = 0;
    uint32_t pf[36];
    uint32_t sK, bE;
    float sc[72];
    auto next_stage = [&]() {
      const int st = k % NSTAGE;
      sK = sbase + st * STAGE_BYTES; bE = bEmpty + 8 * st;
      mbar_wait(bFull + 8 * st, (k / NSTAGE) & 1);
      PROF(2, w, 2 + 3 * k);
    };
    auto issue_s = [&](uint32_t dQ) {
      const uint32_t dK = make_desc(sK, 16, 1024);
#pragma unroll
      for (int kk = 0; kk < 12; ++kk)
        wgmma_ss_n144<0, 0>(sc, dQ + ((kk >> 2) * 512 + (kk & 3) * 2), dK + ((kk >> 2) * (KCH / 16) + (kk & 3) * 2), kk > 0);
      wg_commit();
    };
    auto issue_pv = [&](uint32_t sV, int acc) {
      const uint32_t dV = make_desc(sV, KCH, 1024);
#pragma unroll
      for (int kk = 0; kk < 9; ++kk)
        wgmma_rs_n192<1>(o, pf[4 * kk], pf[4 * kk + 1], pf[4 * kk + 2], pf[4 * kk + 3], dV + kk * 128, acc || (kk > 0));
      wg_commit();
    };
    float a0, a1;
    auto softmax = [&]() {
      float mx0 = sc[0], mx1 = sc[2];
#pragma unroll
      for (int j = 0; j < 18; ++j) {
        mx0 = fmaxf(mx0, fmaxf(sc[4 * j], sc[4 * j + 1]));
        mx1 = fmaxf(mx1, fmaxf(sc[4 * j + 2], sc[4 * j + 3]));
      }
      mx0 = fmaxf(mx0, __shfl_xor_sync(0xffffffffu, mx0, 1)); mx0 = fmaxf(mx0, __shfl_xor_sync(0xffffffffu, mx0, 2));
      mx1 = fmaxf(mx1, __shfl_xor_sync(0xffffffffu, mx1, 1)); mx1 = fmaxf(mx1, __shfl_xor_sync(0xffffffffu, mx1, 2));
      const float mn0 = fmaxf(m0, mx0), mn1 = fmaxf(m1, mx1);
      a0 = ex2((m0 - mn0) * SM_SCALE_LOG2); a1 = ex2((m1 - mn1) * SM_SCALE_LOG2);
      m0 = mn0; m1 = mn1;
      const float ms0 = mn0 * SM_SCALE_LOG2, ms1 = mn1 * SM_SCALE_LOG2;
      float ls0 = 0.f, ls1 = 0.f;
#pragma unroll
      for (int j = 0; j < 18; ++j) {
        sc[4 * j] = ex2(fmaf(sc[4 * j], SM_SCALE_LOG2, -ms0)); sc[4 * j + 1] = ex2(fmaf(sc[4 * j + 1], SM_SCALE_LOG2, -ms0));
        sc[4 * j + 2] = ex2(fmaf(sc[4 * j + 2], SM_SCALE_LOG2, -ms1)); sc[4 * j + 3] = ex2(fmaf(sc[4 * j + 3], SM_SCALE_LOG2, -ms1));
        ls0 += sc[4 * j] + sc[4 * j + 1]; ls1 += sc[4 * j + 2] + sc[4 * j + 3];
      }
      l0 = l0 * a0 + ls0; l1 = l1 * a1 + ls1;
    };
    const uint32_t dQ1 = make_desc(sQt, 16, 1024);
    m0 = m1 = -INFINITY; l0 = l1 = 0.f;
    if (skip0) {
      if (lane == 0) mbar_arrive(bEmpty);
      k = 1;
    }
    mbar_wait((skip0 ? bQ1 : bQ0) + 8 * w, 0);
    PROF(2, w, 1);
    next_stage();
    acquire();
    wg_fence();
    issue_s(skip0 ? dQ1 : make_desc(sbase + 2 * STAGE_BYTES + w * TILE_BYTES, 16, 1024));
    release();
    wg_wait<0>();
    fence_regs(sc);
    PROF(2, w, 3 + 3 * k);
    if (!skip0 && lane == 0) mbar_arrive(bQ0Free);
    softmax();
#pragma unroll
    for (int j = 0; j < 36; ++j) pf[j] = pack_bf16(sc[2 * j], sc[2 * j + 1]);
    ++k;
    mbar_wait(bQ1 + 8 * w, 0);
#pragma unroll 1
    for (; k < ntot; ++k) {
      const uint32_t sV = sK, bEv = bE;
      next_stage();
      acquire();
      wg_fence();
      issue_s(dQ1);
      issue_pv(sV, k > 2);
      release();
      float4 ml0;
      if (k == 1) {
        ml0 = make_float4(m0, m1, l0, l1);
        m0 = m1 = -INFINITY; l0 = l1 = 0.f;
      }
      wg_wait<1>();
      fence_regs(sc);
      PROF(2, w, 3 + 3 * k);
      if (k == ntot - 1 && lane == 0) mbar_arrive_remote(mapa(bXFree, rank ^ 1));
      softmax();
      wg_wait<0>();
      fence_regs(o);
      if (lane == 0) mbar_arrive(bEv);
      if (k == 1) {
        ml0.z += __shfl_xor_sync(0xffffffffu, ml0.z, 1); ml0.z += __shfl_xor_sync(0xffffffffu, ml0.z, 2);
        ml0.w += __shfl_xor_sync(0xffffffffu, ml0.w, 1); ml0.w += __shfl_xor_sync(0xffffffffu, ml0.w, 2);
        const int slot = cl * 3 + (rank ? w : 2);
        if (rank || wl == 0) {
          uint4* po = g_part + (size_t)slot * (12 * 128) + t;
#pragma unroll
          for (int j = 0; j < 12; ++j)
            po[j * 128] = make_uint4(pack_bf16(o[8 * j], o[8 * j + 1]), pack_bf16(o[8 * j + 2], o[8 * j + 3]), pack_bf16(o[8 * j + 4], o[8 * j + 5]), pack_bf16(o[8 * j + 6], o[8 * j + 7]));
          g_pml[slot * 128 + t] = ml0;
        }
        named_arrive(6 + w, 160);
      } else {
#pragma unroll
        for (int j = 0; j < 24; ++j) { o[4 * j] *= a0; o[4 * j + 1] *= a0; o[4 * j + 2] *= a1; o[4 * j + 3] *= a1; }
      }
#pragma unroll
      for (int j = 0; j < 36; ++j) pf[j] = pack_bf16(sc[2 * j], sc[2 * j + 1]);
    }
    acquire();
    wg_fence();
    issue_pv(sK, 1);
    release();
    wg_wait<0>();
    fence_regs(o);
    if (lane == 0) mbar_arrive(bE);
    PROF(2, w, 1 + 3 * k);
    l0 += __shfl_xor_sync(0xffffffffu, l0, 1); l0 += __shfl_xor_sync(0xffffffffu, l0, 2);
    l1 += __shfl_xor_sync(0xffffffffu, l1, 1); l1 += __shfl_xor_sync(0xffffffffu, l1, 2);
    PROF(2, w, 20);
    if (w != rank) {
      mbar_wait_cluster(bXFree, 0);
      const uint32_t rq = mapa(sQ, rank ^ 1) + t * 16, rb = mapa(bXFull, rank ^ 1);
#pragma unroll
      for (int i = 0; i < 12; ++i)
        st_async_v4(rq + i * 2048, __uint_as_float(pack_bf16(o[8 * i], o[8 * i + 1])), __uint_as_float(pack_bf16(o[8 * i + 2], o[8 * i + 3])),
                    __uint_as_float(pack_bf16(o[8 * i + 4], o[8 * i + 5])), __uint_as_float(pack_bf16(o[8 * i + 6], o[8 * i + 7])), rb);
      st_async_v4(mapa(sML, rank ^ 1) + t * 16, m0, m1, l0, l1, rb);
      PROF(2, w, 21);
      if (rank == 0) return;
    }
  }

  const bool recv = (w == rank);
  mbar_wait(bW, 0);
  const uint32_t sT = sW2 + WCH;
  const int grow = f * N_ + (recv ? (128 * c + 64 * w) : (1152 + 16 * c));
  uint32_t af[48];
  if (recv) {
    mbar_wait_cluster(bXFull, 0);
    PROF(2, w, 17);
    const float4 ml = *reinterpret_cast<const float4*>(sptr + P2_ML_OFF + t * 16);
    const float mn0 = fmaxf(m0, ml.x), mn1 = fmaxf(m1, ml.y);
    float a0 = ex2((m0 - mn0) * SM_SCALE_LOG2), a1 = ex2((m1 - mn1) * SM_SCALE_LOG2);
    float b0 = ex2((ml.x - mn0) * SM_SCALE_LOG2), b1 = ex2((ml.y - mn1) * SM_SCALE_LOG2);
    const float i0 = 1.f / (a0 * l0 + b0 * ml.z), i1 = 1.f / (a1 * l1 + b1 * ml.w);
    a0 *= i0; b0 *= i0; a1 *= i1; b1 *= i1;
#pragma unroll
    for (int i = 0; i < 12; ++i) {
      const uint4 v = *reinterpret_cast<const uint4*>(sptr + P2_Q_OFF + i * 2048 + t * 16);
      af[4 * i] = pack_bf16(a0 * o[8 * i] + b0 * bf_lo(v.x), a0 * o[8 * i + 1] + b0 * bf_hi(v.x));
      af[4 * i + 1] = pack_bf16(a1 * o[8 * i + 2] + b1 * bf_lo(v.y), a1 * o[8 * i + 3] + b1 * bf_hi(v.y));
      af[4 * i + 2] = pack_bf16(a0 * o[8 * i + 4] + b0 * bf_lo(v.z), a0 * o[8 * i + 5] + b0 * bf_hi(v.z));
      af[4 * i + 3] = pack_bf16(a1 * o[8 * i + 6] + b1 * bf_lo(v.w), a1 * o[8 * i + 7] + b1 * bf_hi(v.w));
    }
  } else {
    if (t == 0) wait_counter(g_cnt + f, 27);
    named_bar(1 + w, 128);
    const int slot0 = f * 27 + (c >> 2), tl = (c & 3) * 32 + lane;
    float4 mlv[9]; uint4 v[9][3];
#pragma unroll
    for (int i = 0; i < 9; ++i) {
      mlv[i] = __ldcg(g_pml + (slot0 + 3 * i) * 128 + tl);
#pragma unroll
      for (int j = 0; j < 3; ++j) v[i][j] = __ldcg(g_part + (size_t)(slot0 + 3 * i) * (12 * 128) + (wl * 3 + j) * 128 + tl);
    }
    float mn0 = mlv[0].x, mn1 = mlv[0].y;
#pragma unroll
    for (int i = 1; i < 9; ++i) { mn0 = fmaxf(mn0, mlv[i].x); mn1 = fmaxf(mn1, mlv[i].y); }
    float s0 = 0.f, s1 = 0.f;
#pragma unroll
    for (int i = 0; i < 9; ++i) {
      mlv[i].x = ex2((mlv[i].x - mn0) * SM_SCALE_LOG2); mlv[i].y = ex2((mlv[i].y - mn1) * SM_SCALE_LOG2);
      s0 += mlv[i].x * mlv[i].z; s1 += mlv[i].y * mlv[i].w;
    }
    s0 = 1.f / s0; s1 = 1.f / s1;
    uint8_t* pT = sptr + (sT - sbase);
#pragma unroll
    for (int j = 0; j < 3; ++j) {
      float x[8] = {};
#pragma unroll
      for (int i = 0; i < 9; ++i) {
        x[0] += mlv[i].x * bf_lo(v[i][j].x); x[1] += mlv[i].x * bf_hi(v[i][j].x); x[2] += mlv[i].y * bf_lo(v[i][j].y); x[3] += mlv[i].y * bf_hi(v[i][j].y);
        x[4] += mlv[i].x * bf_lo(v[i][j].z); x[5] += mlv[i].x * bf_hi(v[i][j].z); x[6] += mlv[i].y * bf_lo(v[i][j].w); x[7] += mlv[i].y * bf_hi(v[i][j].w);
      }
      const int col = (wl * 3 + j) * 16 + 2 * q;
      *reinterpret_cast<uint32_t*>(pT + g * OPITCH + col * 2) = pack_bf16(x[0] * s0, x[1] * s0);
      *reinterpret_cast<uint32_t*>(pT + (g + 8) * OPITCH + col * 2) = pack_bf16(x[2] * s1, x[3] * s1);
      *reinterpret_cast<uint32_t*>(pT + g * OPITCH + col * 2 + 16) = pack_bf16(x[4] * s0, x[5] * s0);
      *reinterpret_cast<uint32_t*>(pT + (g + 8) * OPITCH + col * 2 + 16) = pack_bf16(x[6] * s1, x[7] * s1);
    }
    named_bar(1 + w, 128);
#pragma unroll
    for (int j = 0; j < 24; ++j) {
      af[2 * j] = *reinterpret_cast<const uint32_t*>(pT + g * OPITCH + j * 16 + q * 4);
      af[2 * j + 1] = *reinterpret_cast<const uint32_t*>(pT + (g + 8) * OPITCH + j * 16 + q * 4);
    }
  }
  PROF(2, w, 18);
  gemm_rs_w(o, af, sW0, sW1, sW2);
  const int nit = recv ? 12 : 3;
  uint4 xv[12];
  {
    const uint4* src = reinterpret_cast<const uint4*>(g_x1 + (size_t)grow * C_) + t;
#pragma unroll
    for (int it = 0; it < 12; ++it) if (it < nit) xv[it] = __ldcg(src + it * 128);
  }
  named_bar(1 + w, 128);
  wg_wait<0>();
  fence_regs(o);
  PROF(2, w, 22);
  const uint32_t sS = recv ? sQ : sT;
  if (recv || wl == 0) {
    const uint32_t addr = sS + (wl * 16 + ((lane >> 3) & 1) * 8 + (lane & 7)) * OPITCH + (lane >> 4) * 16;
#pragma unroll
    for (int i = 0; i < 12; ++i)
      stsm_x4(addr + i * 32, pack_bf16(o[8 * i], o[8 * i + 1]), pack_bf16(o[8 * i + 2], o[8 * i + 3]),
              pack_bf16(o[8 * i + 4], o[8 * i + 5]), pack_bf16(o[8 * i + 6], o[8 * i + 7]));
  }
  named_bar(1 + w, 128);
  {
    const uint8_t* pS = sptr + (sS - sbase);
    uint4* dst = reinterpret_cast<uint4*>(out + (size_t)grow * C_);
#pragma unroll
    for (int it = 0; it < 12; ++it) {
      if (it < nit) {
        const int unit = it * 128 + t, row = unit / 24, u = unit - row * 24;
        const uint4 y = *reinterpret_cast<const uint4*>(pS + row * OPITCH + u * 16);
        dst[unit] = make_uint4(add_bf2(xv[it].x, y.x), add_bf2(xv[it].y, y.y), add_bf2(xv[it].z, y.z), add_bf2(xv[it].w, y.w));
      }
    }
  }
  PROF(2, w, 23);
}

}

extern "C" void kernel_launch(void* const* d_in, const int* in_sizes, int n_in, void* d_out, int out_size) {
  using namespace tsf;
  const __nv_bfloat16* x = (const __nv_bfloat16*)d_in[0];
  const __nv_bfloat16* wqkv_t = (const __nv_bfloat16*)d_in[1];
  const __nv_bfloat16* wo_t = (const __nv_bfloat16*)d_in[2];
  const __nv_bfloat16* wqkv_s = (const __nv_bfloat16*)d_in[3];
  const __nv_bfloat16* wo_s = (const __nv_bfloat16*)d_in[4];
  __nv_bfloat16* out = (__nv_bfloat16*)d_out;
  static bool init = false;
  if (!init) {
    cudaFuncSetAttribute(p1_kernel, cudaFuncAttributeMaxDynamicSharedMemorySize, P1_SMEM);
    cudaFuncSetAttribute(p2_kernel, cudaFuncAttributeMaxDynamicSharedMemorySize, P2_SMEM);
    cudaFuncSetAttribute(p1_kernel, cudaFuncAttributePreferredSharedMemoryCarveout, cudaSharedmemCarveoutMaxShared);
    cudaFuncSetAttribute(p2_kernel, cudaFuncAttributePreferredSharedMemoryCarveout, cudaSharedmemCarveoutMaxShared);
    init = true;
  }
  cudaStream_t st = cudaStreamPerThread;
  p1_kernel<<<120, 384, P1_SMEM, st>>>(x, wqkv_t, wo_t, wqkv_s, wo_s);
  cudaLaunchAttribute at[1];
  at[0].id = cudaLaunchAttributeProgrammaticStreamSerialization;
  at[0].val.programmaticStreamSerializationAllowed = 1;
  {
    cudaLaunchConfig_t cfg = {};
    cfg.gridDim = dim3(126); cfg.blockDim = dim3(384); cfg.dynamicSmemBytes = P2_SMEM; cfg.stream = st;
    cfg.attrs = at; cfg.numAttrs = 1;
    cudaLaunchKernelEx(&cfg, p2_kernel, out);
  }
}
```

```cpp
#include <cuda_runtime.h>
#include <cuda_bf16.h>
#include <stdint.h>

namespace tsf {

constexpr int T_ = 7, N_ = 1296, C_ = 192, ROWS = T_ * N_;
constexpr float SM_SCALE_LOG2 = 0.07216878364870322f * 1.4426950408889634f;
constexpr uint32_t SPIN_LIMIT = 1u << 24;

__device__ __align__(1024) __nv_bfloat16 g_w[4 * 3 * 192 * 64];
__device__ __align__(1024) __nv_bfloat16 g_x1[ROWS * C_];
__device__ __align__(1024) __nv_bfloat16 g_h2[T_ * 3 * N_ * 64];
__device__ __align__(1024) __nv_bfloat16 g_q2[T_ * 3 * N_ * 64 + 64 * 64];
__device__ __align__(1024) uint4 g_part[189 * 12 * 128];
__device__ float4 g_pml[189 * 128];
__device__ unsigned int g_cnt[24];

#define PROF(kern, slot, idx)
__device__ __forceinline__ uint32_t smem_u32(const void* p) { return (uint32_t)__cvta_generic_to_shared(p); }
__device__ __forceinline__ void mbar_init(uint32_t bar, uint32_t count) {
  asm volatile("mbarrier.init.shared::cta.b64 [%0], %1;" ::"r"(bar), "r"(count) : "memory");
}
__device__ __forceinline__ void mbar_expect_tx(uint32_t bar, uint32_t bytes) {
  asm volatile("mbarrier.arrive.expect_tx.shared::cta.b64 _, [%0], %1;" ::"r"(bar), "r"(bytes) : "memory");
}
__device__ __forceinline__ void mbar_arrive(uint32_t bar) {
  asm volatile("mbarrier.arrive.shared::cta.b64 _, [%0];" ::"r"(bar) : "memory");
}
__device__ __forceinline__ void mbar_arrive_remote(uint32_t rbar) {
  asm volatile("mbarrier.arrive.release.cluster.shared::cluster.b64 _, [%0];" ::"r"(rbar) : "memory");
}
__device__ __forceinline__ bool mbar_try(uint32_t bar, uint32_t parity) {
  uint32_t ok;
  asm volatile("{\n.reg .pred p;\nmbarrier.try_wait.parity.shared::cta.b64 p, [%1], %2;\nselp.u32 %0, 1, 0, p;\n}\n"
               : "=r"(ok) : "r"(bar), "r"(parity) : "memory");
  return ok != 0;
}
__device__ __forceinline__ bool mbar_try_cluster(uint32_t bar, uint32_t parity) {
  uint32_t ok;
  asm volatile("{\n.reg .pred p;\nmbarrier.try_wait.parity.acquire.cluster.shared::cta.b64 p, [%1], %2;\nselp.u32 %0, 1, 0, p;\n}\n"
               : "=r"(ok) : "r"(bar), "r"(parity) : "memory");
  return ok != 0;
}
__device__ __forceinline__ void mbar_wait(uint32_t bar, uint32_t parity) {
#pragma unroll 1
  for (uint32_t it = 0; it < SPIN_LIMIT; ++it)
    if (mbar_try(bar, parity)) return;
  __trap();
}
__device__ __forceinline__ void mbar_wait_cluster(uint32_t bar, uint32_t parity) {
#pragma unroll 1
  for (uint32_t it = 0; it < SPIN_LIMIT; ++it)
    if (mbar_try_cluster(bar, parity)) return;
  __trap();
}
__device__ __forceinline__ void bulk_g2s(uint32_t dst, const void* src, uint32_t bytes, uint32_t bar) {
  asm volatile("cp.async.bulk.shared::cluster.global.mbarrier::complete_tx::bytes [%0], [%1], %2, [%3];"
               ::"r"(dst), "l"(src), "r"(bytes), "r"(bar) : "memory");
}
__device__ __forceinline__ void fence_async_smem() { asm volatile("fence.proxy.async.shared::cta;" ::: "memory"); }
__device__ __forceinline__ void fence_mbar_init() { asm volatile("fence.mbarrier_init.release.cluster;" ::: "memory"); }
__device__ __forceinline__ void named_bar(int id, int n) { asm volatile("bar.sync %0, %1;" ::"r"(id), "r"(n) : "memory"); }
__device__ __forceinline__ void wg_fence() { asm volatile("wgmma.fence.sync.aligned;" ::: "memory"); }
__device__ __forceinline__ void wg_commit() { asm volatile("wgmma.commit_group.sync.aligned;" ::: "memory"); }
template <int N> __device__ __forceinline__ void wg_wait() { asm volatile("wgmma.wait_group.sync.aligned %0;" ::"n"(N) : "memory"); }
template <int N> __device__ __forceinline__ void fence_regs(float (&d)[N]) {
#pragma unroll
  for (int i = 0; i < N; ++i) asm volatile("" : "+f"(d[i])::"memory");
}
__device__ __forceinline__ void pdl_wait() { asm volatile("griddepcontrol.wait;" ::: "memory"); }
__device__ __forceinline__ void pdl_launch() { asm volatile("griddepcontrol.launch_dependents;" ::: "memory"); }
__device__ __forceinline__ uint32_t mapa(uint32_t addr, uint32_t rank) {
  uint32_t r;
  asm volatile("mapa.shared::cluster.u32 %0, %1, %2;" : "=r"(r) : "r"(addr), "r"(rank));
  return r;
}
__device__ __forceinline__ void cluster_sync_all() {
  asm volatile("barrier.cluster.arrive.release.aligned;\nbarrier.cluster.wait.acquire.aligned;" ::: "memory");
}
__device__ __forceinline__ void st_cluster_v4(uint32_t addr, float a, float b, float c, float d) {
  asm volatile("st.shared::cluster.v4.f32 [%0], {%1, %2, %3, %4};" ::"r"(addr), "f"(a), "f"(b), "f"(c), "f"(d) : "memory");
}
__device__ __forceinline__ void st_async_v4(uint32_t addr, float a, float b, float c, float d, uint32_t rbar) {
  asm volatile("st.async.weak.shared::cluster.mbarrier::complete_tx::bytes.v4.f32 [%0], {%1, %2, %3, %4}, [%5];"
               ::"r"(addr), "f"(a), "f"(b), "f"(c), "f"(d), "r"(rbar) : "memory");
}
__device__ __forceinline__ uint32_t make_desc(uint32_t addr, uint32_t lbo, uint32_t) {
  return ((addr & 0x3FFFF) >> 4) | ((lbo >> 4) << 16);
}
__device__ __forceinline__ uint32_t pack_bf16(float lo, float hi) {
  uint32_t r;
  asm("cvt.rn.bf16x2.f32 %0, %1, %2;" : "=r"(r) : "f"(hi), "f"(lo));
  return r;
}
__device__ __forceinline__ float bf_lo(uint32_t v) { return __uint_as_float(v << 16); }
__device__ __forceinline__ float bf_hi(uint32_t v) { return __uint_as_float(v & 0xffff0000u); }
__device__ __forceinline__ float ex2(float x) {
  float r;
  asm("ex2.approx.ftz.f32 %0, %1;" : "=f"(r) : "f"(x));
  return r;
}
__device__ __forceinline__ void stsm_x4(uint32_t addr, uint32_t r0, uint32_t r1, uint32_t r2, uint32_t r3) {
  asm volatile("stmatrix.sync.aligned.m8n8.x4.shared.b16 [%0], {%1, %2, %3, %4};" ::"r"(addr), "r"(r0), "r"(r1), "r"(r2), "r"(r3) : "memory");
}
__device__ __forceinline__ void bulk_s2g(void* dst, uint32_t src, uint32_t bytes) {
  asm volatile("cp.async.bulk.global.shared::cta.bulk_group [%0], [%1], %2;" ::"l"(dst), "r"(src), "r"(bytes) : "memory");
}
__device__ __forceinline__ void bulk_commit() { asm volatile("cp.async.bulk.commit_group;" ::: "memory"); }
__device__ __forceinline__ void bulk_wait_read() { asm volatile("cp.async.bulk.wait_group.read 0;" ::: "memory"); }
__device__ __forceinline__ void bulk_wait_all() { asm volatile("cp.async.bulk.wait_group 0;" ::: "memory"); }
__device__ __forceinline__ void named_arrive(int id, int n) { asm volatile("bar.arrive %0, %1;" ::"r"(id), "r"(n) : "memory"); }
__device__ __forceinline__ void wait_counter(const unsigned int* p, unsigned int target) {
#pragma unroll 1
  for (uint32_t it = 0; it < SPIN_LIMIT; ++it) {
    unsigned int v;
    asm volatile("ld.acquire.gpu.global.u32 %0, [%1];" : "=r"(v) : "l"(p) : "memory");
    if (v >= target) return;
    __nanosleep(32);
  }
  __trap();
}
__device__ __forceinline__ void fence_async_all() { asm volatile("fence.proxy.async;" ::: "memory"); }
__device__ __forceinline__ int swz(int row, int col) { return row * 64 + ((((col >> 3) ^ row) & 7) << 3) + (col & 7); }

template <int TA, int TB>
__device__ __forceinline__ void wgmma_ss_n48(float (&d)[24], uint32_t da, uint32_t db, int sc) {
  asm volatile("{\n.reg .pred p;\n.reg .b64 da, db;\n.reg .b32 hi;\nmov.b32 hi, 0x40000040;\nmov.b64 da, {%24, hi};\nmov.b64 db, {%25, hi};\nsetp.ne.b32 p, %26, 0;\n"
    "wgmma.mma_async.sync.aligned.m64n48k16.f32.bf16.bf16 "
    "{%0, %1, %2, %3, %4, %5, %6, %7, %8, %9, %10, %11, %12, %13, %14, %15, %16, %17, %18, %19, %20, %21, %22, %23}, "
    "da, db, p, 1, 1, %27, %28;\n}\n"
    : "+f"(d[0]), "+f"(d[1]), "+f"(d[2]), "+f"(d[3]), "+f"(d[4]), "+f"(d[5]), "+f"(d[6]), "+f"(d[7]), "+f"(d[8]), "+f"(d[9]), "+f"(d[10]), "+f"(d[11]), "+f"(d[12]), "+f"(d[13]), "+f"(d[14]), "+f"(d[15]), "+f"(d[16]), "+f"(d[17]), "+f"(d[18]), "+f"(d[19]), "+f"(d[20]), "+f"(d[21]), "+f"(d[22]), "+f"(d[23])
    : "r"(da), "r"(db), "r"(sc), "n"(TA), "n"(TB));
}
template <int TA, int TB>
__device__ __forceinline__ void wgmma_ss_n192(float (&d)[96], uint32_t da, uint32_t db, int sc) {
  asm volatile("{\n.reg .pred p;\n.reg .b64 da, db;\n.reg .b32 hi;\nmov.b32 hi, 0x40000040;\nmov.b64 da, {%96, hi};\nmov.b64 db, {%97, hi};\nsetp.ne.b32 p, %98, 0;\n"
    "wgmma.mma_async.sync.aligned.m64n192k16.f32.bf16.bf16 "
    "{%0, %1, %2, %3, %4, %5, %6, %7, %8, %9, %10, %11, %12, %13, %14, %15, %16, %17, %18, %19, %20, %21, %22, %23, %24, %25, %26, %27, %28, %29, %30, %31, %32, %33, %34, %35, %36, %37, %38, %39, %40, %41, %42, %43, %44, %45, %46, %47, %48, %49, %50, %51, %52, %53, %54, %55, %56, %57, %58, %59, %60, %61, %62, %63, %64, %65, %66, %67, %68, %69, %70, %71, %72, %73, %74, %75, %76, %77, %78, %79, %80, %81, %82, %83, %84, %85, %86, %87, %88, %89, %90, %91, %92, %93, %94, %95}, "
    "da, db, p, 1, 1, %99, %100;\n}\n"
    : "+f"(d[0]), "+f"(d[1]), "+f"(d[2]), "+f"(d[3]), "+f"(d[4]), "+f"(d[5]), "+f"(d[6]), "+f"(d[7]), "+f"(d[8]), "+f"(d[9]), "+f"(d[10]), "+f"(d[11]), "+f"(d[12]), "+f"(d[13]), "+f"(d[14]), "+f"(d[15]), "+f"(d[16]), "+f"(d[17]), "+f"(d[18]), "+f"(d[19]), "+f"(d[20]), "+f"(d[21]), "+f"(d[22]), "+f"(d[23]), "+f"(d[24]), "+f"(d[25]), "+f"(d[26]), "+f"(d[27]), "+f"(d[28]), "+f"(d[29]), "+f"(d[30]), "+f"(d[31]), "+f"(d[32]), "+f"(d[33]), "+f"(d[34]), "+f"(d[35]), "+f"(d[36]), "+f"(d[37]), "+f"(d[38]), "+f"(d[39]), "+f"(d[40]), "+f"(d[41]), "+f"(d[42]), "+f"(d[43]), "+f"(d[44]), "+f"(d[45]), "+f"(d[46]), "+f"(d[47]), "+f"(d[48]), "+f"(d[49]), "+f"(d[50]), "+f"(d[51]), "+f"(d[52]), "+f"(d[53]), "+f"(d[54]), "+f"(d[55]), "+f"(d[56]), "+f"(d[57]), "+f"(d[58]), "+f"(d[59]), "+f"(d[60]), "+f"(d[61]), "+f"(d[62]), "+f"(d[63]), "+f"(d[64]), "+f"(d[65]), "+f"(d[66]), "+f"(d[67]), "+f"(d[68]), "+f"(d[69]), "+f"(d[70]), "+f"(d[71]), "+f"(d[72]), "+f"(d[73]), "+f"(d[74]), "+f"(d[75]), "+f"(d[76]), "+f"(d[77]), "+f"(d[78]), "+f"(d[79]), "+f"(d[80]), "+f"(d[81]), "+f"(d[82]), "+f"(d[83]), "+f"(d[84]), "+f"(d[85]), "+f"(d[86]), "+f"(d[87]), "+f"(d[88]), "+f"(d[89]), "+f"(d[90]), "+f"(d[91]), "+f"(d[92]), "+f"(d[93]), "+f"(d[94]), "+f"(d[95])
    : "r"(da), "r"(db), "r"(sc), "n"(TA), "n"(TB));
}
template <int TB>
__device__ __forceinline__ void wgmma_rs_n192(float (&d)[96], uint32_t a0, uint32_t a1, uint32_t a2, uint32_t a3, uint32_t db, int sc) {
  asm volatile("{\n.reg .pred p;\n.reg .b64 db;\n.reg .b32 hi;\nmov.b32 hi, 0x40000040;\nmov.b64 db, {%100, hi};\nsetp.ne.b32 p, %101, 0;\n"
    "wgmma.mma_async.sync.aligned.m64n192k16.f32.bf16.bf16 "
    "{%0, %1, %2, %3, %4, %5, %6, %7, %8, %9, %10, %11, %12, %13, %14, %15, %16, %17, %18, %19, %20, %21, %22, %23, %24, %25, %26, %27, %28, %29, %30, %31, %32, %33, %34, %35, %36, %37, %38, %39, %40, %41, %42, %43, %44, %45, %46, %47, %48, %49, %50, %51, %52, %53, %54, %55, %56, %57, %58, %59, %60, %61, %62, %63, %64, %65, %66, %67, %68, %69, %70, %71, %72, %73, %74, %75, %76, %77, %78, %79, %80, %81, %82, %83, %84, %85, %86, %87, %88, %89, %90, %91, %92, %93, %94, %95}, "
    "{%96, %97, %98, %99}, db, p, 1, 1, %102;\n}\n"
    : "+f"(d[0]), "+f"(d[1]), "+f"(d[2]), "+f"(d[3]), "+f"(d[4]), "+f"(d[5]), "+f"(d[6]), "+f"(d[7]), "+f"(d[8]), "+f"(d[9]), "+f"(d[10]), "+f"(d[11]), "+f"(d[12]), "+f"(d[13]), "+f"(d[14]), "+f"(d[15]), "+f"(d[16]), "+f"(d[17]), "+f"(d[18]), "+f"(d[19]), "+f"(d[20]), "+f"(d[21]), "+f"(d[22]), "+f"(d[23]), "+f"(d[24]), "+f"(d[25]), "+f"(d[26]), "+f"(d[27]), "+f"(d[28]), "+f"(d[29]), "+f"(d[30]), "+f"(d[31]), "+f"(d[32]), "+f"(d[33]), "+f"(d[34]), "+f"(d[35]), "+f"(d[36]), "+f"(d[37]), "+f"(d[38]), "+f"(d[39]), "+f"(d[40]), "+f"(d[41]), "+f"(d[42]), "+f"(d[43]), "+f"(d[44]), "+f"(d[45]), "+f"(d[46]), "+f"(d[47]), "+f"(d[48]), "+f"(d[49]), "+f"(d[50]), "+f"(d[51]), "+f"(d[52]), "+f"(d[53]), "+f"(d[54]), "+f"(d[55]), "+f"(d[56]), "+f"(d[57]), "+f"(d[58]), "+f"(d[59]), "+f"(d[60]), "+f"(d[61]), "+f"(d[62]), "+f"(d[63]), "+f"(d[64]), "+f"(d[65]), "+f"(d[66]), "+f"(d[67]), "+f"(d[68]), "+f"(d[69]), "+f"(d[70]), "+f"(d[71]), "+f"(d[72]), "+f"(d[73]), "+f"(d[74]), "+f"(d[75]), "+f"(d[76]), "+f"(d[77]), "+f"(d[78]), "+f"(d[79]), "+f"(d[80]), "+f"(d[81]), "+f"(d[82]), "+f"(d[83]), "+f"(d[84]), "+f"(d[85]), "+f"(d[86]), "+f"(d[87]), "+f"(d[88]), "+f"(d[89]), "+f"(d[90]), "+f"(d[91]), "+f"(d[92]), "+f"(d[93]), "+f"(d[94]), "+f"(d[95])
    : "r"(a0), "r"(a1), "r"(a2), "r"(a3), "r"(db), "r"(sc), "n"(TB));
}
template <int TB>
__device__ __forceinline__ void wgmma_rs_n64(float (&d)[32], uint32_t a0, uint32_t a1, uint32_t a2, uint32_t a3, uint32_t db, int sc) {
  asm volatile("{\n.reg .pred p;\n.reg .b64 db;\n.reg .b32 hi;\nmov.b32 hi, 0x40000040;\nmov.b64 db, {%36, hi};\nsetp.ne.b32 p, %37, 0;\n"
    "wgmma.mma_async.sync.aligned.m64n64k16.f32.bf16.bf16 "
    "{%0, %1, %2, %3, %4, %5, %6, %7, %8, %9, %10, %11, %12, %13, %14, %15, %16, %17, %18, %19, %20, %21, %22, %23, %24, %25, %26, %27, %28, %29, %30, %31}, "
    "{%32, %33, %34, %35}, db, p, 1, 1, %38;\n}\n"
    : "+f"(d[0]), "+f"(d[1]), "+f"(d[2]), "+f"(d[3]), "+f"(d[4]), "+f"(d[5]), "+f"(d[6]), "+f"(d[7]), "+f"(d[8]), "+f"(d[9]), "+f"(d[10]), "+f"(d[11]), "+f"(d[12]), "+f"(d[13]), "+f"(d[14]), "+f"(d[15]), "+f"(d[16]), "+f"(d[17]), "+f"(d[18]), "+f"(d[19]), "+f"(d[20]), "+f"(d[21]), "+f"(d[22]), "+f"(d[23]), "+f"(d[24]), "+f"(d[25]), "+f"(d[26]), "+f"(d[27]), "+f"(d[28]), "+f"(d[29]), "+f"(d[30]), "+f"(d[31])
    : "r"(a0), "r"(a1), "r"(a2), "r"(a3), "r"(db), "r"(sc), "n"(TB));
}
template <int TA, int TB>
__device__ __forceinline__ void wgmma_ss_n144(float (&d)[72], uint32_t da, uint32_t db, int sc) {
  asm volatile("{\n.reg .pred p;\n.reg .b64 da, db;\n.reg .b32 hi;\nmov.b32 hi, 0x40000040;\nmov.b64 da, {%72, hi};\nmov.b64 db, {%73, hi};\nsetp.ne.b32 p, %74, 0;\n"
    "wgmma.mma_async.sync.aligned.m64n144k16.f32.bf16.bf16 "
    "{%0, %1, %2, %3, %4, %5, %6, %7, %8, %9, %10, %11, %12, %13, %14, %15, %16, %17, %18, %19, %20, %21, %22, %23, %24, %25, %26, %27, %28, %29, %30, %31, %32, %33, %34, %35, %36, %37, %38, %39, %40, %41, %42, %43, %44, %45, %46, %47, %48, %49, %50, %51, %52, %53, %54, %55, %56, %57, %58, %59, %60, %61, %62, %63, %64, %65, %66, %67, %68, %69, %70, %71}, "
    "da, db, p, 1, 1, %75, %76;\n}\n"
    : "+f"(d[0]), "+f"(d[1]), "+f"(d[2]), "+f"(d[3]), "+f"(d[4]), "+f"(d[5]), "+f"(d[6]), "+f"(d[7]), "+f"(d[8]), "+f"(d[9]), "+f"(d[10]), "+f"(d[11]), "+f"(d[12]), "+f"(d[13]), "+f"(d[14]), "+f"(d[15]), "+f"(d[16]), "+f"(d[17]), "+f"(d[18]), "+f"(d[19]), "+f"(d[20]), "+f"(d[21]), "+f"(d[22]), "+f"(d[23]), "+f"(d[24]), "+f"(d[25]), "+f"(d[26]), "+f"(d[27]), "+f"(d[28]), "+f"(d[29]), "+f"(d[30]), "+f"(d[31]), "+f"(d[32]), "+f"(d[33]), "+f"(d[34]), "+f"(d[35]), "+f"(d[36]), "+f"(d[37]), "+f"(d[38]), "+f"(d[39]), "+f"(d[40]), "+f"(d[41]), "+f"(d[42]), "+f"(d[43]), "+f"(d[44]), "+f"(d[45]), "+f"(d[46]), "+f"(d[47]), "+f"(d[48]), "+f"(d[49]), "+f"(d[50]), "+f"(d[51]), "+f"(d[52]), "+f"(d[53]), "+f"(d[54]), "+f"(d[55]), "+f"(d[56]), "+f"(d[57]), "+f"(d[58]), "+f"(d[59]), "+f"(d[60]), "+f"(d[61]), "+f"(d[62]), "+f"(d[63]), "+f"(d[64]), "+f"(d[65]), "+f"(d[66]), "+f"(d[67]), "+f"(d[68]), "+f"(d[69]), "+f"(d[70]), "+f"(d[71])
    : "r"(da), "r"(db), "r"(sc), "n"(TA), "n"(TB));
}

__device__ __forceinline__ void fuse_weights(uint32_t sbase, uint8_t* sptr, int j, const __nv_bfloat16* __restrict__ wqkv_t,
                                             const __nv_bfloat16* __restrict__ wo_t, const __nv_bfloat16* __restrict__ wqkv_s,
                                             const __nv_bfloat16* __restrict__ wo_s) {
  const int m = j / 12, n0 = ((j % 12) >> 2) * 64, k0 = (j & 3) * 48;
  const __nv_bfloat16* wqkv = (m < 2) ? wqkv_t : wqkv_s;
  const __nv_bfloat16* wo = (m < 2) ? wo_t : wo_s;
  const int tid = threadIdx.x;
  const bool odd = m & 1;
  uint8_t* pA = sptr; uint8_t* pB = sptr + 24576;
  uint4 va[4], vb[3];
#pragma unroll
  for (int i = 0; i < 4; ++i) {
    const int u = tid + i * 384;
    const int row = odd ? (u >> 3) : (u / 24), cu = odd ? (u & 7) : (u % 24);
    va[i] = __ldg(reinterpret_cast<const uint4*>(odd ? (wo + row * 192 + n0 + cu * 8) : (wqkv + (n0 + row) * 576 + 192 + cu * 8)));
  }
#pragma unroll
  for (int i = 0; i < 3; ++i) {
    const int u = tid + i * 384, row = u / 24, cu = u % 24;
    vb[i] = __ldg(reinterpret_cast<const uint4*>(wqkv + (k0 + row) * 576 + (odd ? 384 : 0) + cu * 8));
  }
#pragma unroll
  for (int i = 0; i < 4; ++i) {
    const int u = tid + i * 384;
    const int row = odd ? (u >> 3) : (u / 24), cu = odd ? (u & 7) : (u % 24);
    *reinterpret_cast<uint4*>(pA + (cu >> 3) * 8192 + row * 128 + (((cu ^ row) & 7) << 4)) = va[i];
  }
#pragma unroll
  for (int i = 0; i < 3; ++i) {
    const int u = tid + i * 384, row = u / 24, cu = u % 24;
    *reinterpret_cast<uint4*>(pB + (cu >> 3) * 6144 + row * 128 + (((cu ^ row) & 7) << 4)) = vb[i];
  }
  fence_async_smem();
  __syncthreads();
  if (tid < 128) {
    float acc[24];
    const uint32_t dB = make_desc(sbase + 24576, 16, 1024);
    wg_fence();
    if (odd) {
      const uint32_t dA = make_desc(sbase, 8192, 1024);
#pragma unroll
      for (int kk = 0; kk < 12; ++kk) wgmma_ss_n48<1, 0>(acc, dA + kk * 128, dB + ((kk >> 2) * 384 + (kk & 3) * 2), kk > 0);
    } else {
      const uint32_t dA = make_desc(sbase, 16, 1024);
#pragma unroll
      for (int kk = 0; kk < 12; ++kk) wgmma_ss_n48<0, 0>(acc, dA + ((kk >> 2) * 512 + (kk & 3) * 2), dB + ((kk >> 2) * 384 + (kk & 3) * 2), kk > 0);
    }
    wg_commit();
    wg_wait<0>();
    fence_regs(acc);
    const int lane = tid & 31, r0 = n0 + (tid >> 5) * 16 + (lane >> 2);
    __nv_bfloat16* dst = g_w + (size_t)m * 3 * 192 * 64;
#pragma unroll
    for (int jj = 0; jj < 6; ++jj) {
      const int k = k0 + 8 * jj + 2 * (lane & 3);
      __nv_bfloat16* ch = dst + (k >> 6) * (192 * 64);
      *reinterpret_cast<uint32_t*>(ch + swz(r0, k & 63)) = pack_bf16(acc[4 * jj], acc[4 * jj + 1]);
      *reinterpret_cast<uint32_t*>(ch + swz(r0 + 8, k & 63)) = pack_bf16(acc[4 * jj + 2], acc[4 * jj + 3]);
    }
    __threadfence();
    named_bar(1, 128);
    if (tid == 0) atomicAdd(g_cnt + 16 + m, 1u);
  }
}

constexpr int W_BYTES = 3 * 192 * 128;
constexpr int WCH = 192 * 128;
constexpr int TILE_BYTES = 3 * 64 * 128;
constexpr int P1_SMEM = 2 * W_BYTES + 3 * TILE_BYTES + 128 + 1024;
constexpr int FS = 3472;

__device__ __forceinline__ void gemm_rs_w(float (&acc)[96], const uint32_t (&a)[48], uint32_t c0, uint32_t c1, uint32_t c2) {
  wg_fence();
#pragma unroll
  for (int kk = 0; kk < 12; ++kk) {
    const uint32_t base = (kk < 4) ? c0 : ((kk < 8) ? c1 : c2);
    wgmma_rs_n192<0>(acc, a[4 * kk], a[4 * kk + 1], a[4 * kk + 2], a[4 * kk + 3], make_desc(base + (kk & 3) * 32, 16, 1024), kk > 0);
  }
  wg_commit();
}
__device__ __forceinline__ void gemm_ss_w(float (&acc)[96], uint32_t atile, uint32_t c0, uint32_t c1, uint32_t c2) {
  wg_fence();
#pragma unroll
  for (int kk = 0; kk < 12; ++kk) {
    const uint32_t base = (kk < 4) ? c0 : ((kk < 8) ? c1 : c2);
    wgmma_ss_n192<0, 0>(acc, make_desc(atile + (kk >> 2) * 8192 + (kk & 3) * 32, 16, 1024), make_desc(base + (kk & 3) * 32, 16, 1024), kk > 0);
  }
  wg_commit();
}

__global__ void __launch_bounds__(384, 1) p1_kernel(const __nv_bfloat16* __restrict__ x, const __nv_bfloat16* __restrict__ wqkv_t,
                                                    const __nv_bfloat16* __restrict__ wo_t, const __nv_bfloat16* __restrict__ wqkv_s,
                                                    const __nv_bfloat16* __restrict__ wo_s) {
  extern __shared__ uint8_t smem_raw[];
  const uint32_t sbase = (smem_u32(smem_raw) + 1023) & ~1023u;
  uint8_t* sptr = smem_raw + (sbase - smem_u32(smem_raw));
  if (blockIdx.x < 48) {
    PROF(0, 0, 0);
    pdl_launch();
    if (blockIdx.x == 0 && threadIdx.x >= 256 && threadIdx.x < 272) g_cnt[threadIdx.x - 256] = 0;
    fuse_weights(sbase, sptr, blockIdx.x, wqkv_t, wo_t, wqkv_s, wo_s);
    PROF(0, 0, 1);
    return;
  }
  const int bid = blockIdx.x - 48;
  const uint32_t sWA = sbase, sWB = sbase + W_BYTES, sH = sbase + 2 * W_BYTES;
  const uint32_t sX = sH + 2 * TILE_BYTES;
  const uint32_t bars = sH + 3 * TILE_BYTES;
  const int tid = threadIdx.x, warp = tid >> 5, lane = tid & 31;
  if (tid == 0) PROF(1, 3, 0);
  pdl_launch();
  if (tid == 0) {
    mbar_init(bars, 1); mbar_init(bars + 8, 1); mbar_init(bars + 16, 1); mbar_init(bars + 24, 8); mbar_init(bars + 32, 4); mbar_init(bars + 40, 4);
    mbar_init(bars + 48, 1); mbar_init(bars + 56, 1); mbar_init(bars + 64, 8); mbar_init(bars + 72, 1); mbar_init(bars + 80, 1);
    fence_mbar_init();
  }
  __syncthreads();

  if (warp >= 8) {
    asm volatile("setmaxnreg.dec.sync.aligned.u32 40;");
    if (warp == 8 && lane == 0) {
#pragma unroll 1
      for (int i = 0; i < 14; ++i) {
        const int wg = i / 7, tt = i - wg * 7;
        if (tt == 0) mbar_expect_tx(bars + 48 + 8 * wg, 7 * 3456);
        bulk_g2s(sWB + wg * TILE_BYTES + tt * FS, x + ((size_t)tt * N_ + (bid * 2 + wg) * 9) * C_, 3456, bars + 48 + 8 * wg);
      }
      wait_counter(g_cnt + 16, 12);
      fence_async_all();
      mbar_expect_tx(bars, WCH);
      bulk_g2s(sWA, g_w, WCH, bars);
      mbar_expect_tx(bars + 72, WCH);
      bulk_g2s(sWA + WCH, g_w + 192 * 64, WCH, bars + 72);
      mbar_expect_tx(bars + 80, WCH);
      bulk_g2s(sWA + 2 * WCH, g_w + 2 * 192 * 64, WCH, bars + 80);
      wait_counter(g_cnt + 17, 12);
      fence_async_all();
      mbar_wait(bars + 64, 0);
      mbar_expect_tx(bars + 8, W_BYTES);
      bulk_g2s(sWB, g_w + 3 * 192 * 64, W_BYTES, bars + 8);
      wait_counter(g_cnt + 18, 12);
      fence_async_all();
      mbar_wait(bars + 24, 0);
      mbar_expect_tx(bars + 16, W_BYTES);
      bulk_g2s(sWA, g_w + 2 * 3 * 192 * 64, W_BYTES, bars + 16);
    }
    __syncwarp();
#pragma unroll 1
    for (int wg = 0; wg < 2; ++wg) {
      named_bar(6 + 4 * wg, 256);
      const int ht = tid - 256, n0 = (bid * 2 + wg) * 9;
      const uint8_t* pX1 = sptr + 2 * W_BYTES + wg * TILE_BYTES;
      const uint8_t* pH2 = wg ? (sptr + W_BYTES + TILE_BYTES) : (sptr + 2 * W_BYTES + 2 * TILE_BYTES);
#pragma unroll 4
      for (int it = 0; it < 12; ++it) {
        const int idx = it * 128 + ht;
        if (idx < 1512) {
          const int i = idx / 72, off = idx - i * 72, tt = i / 3, ch = i - tt * 3;
          const int so = tt * FS + ch * 1152 + off * 16;
          const uint4 a = *reinterpret_cast<const uint4*>(pX1 + so), b = *reinterpret_cast<const uint4*>(pH2 + so);
          reinterpret_cast<uint4*>(g_h2 + ((size_t)i * N_ + n0) * 64)[off] = b;
          reinterpret_cast<uint4*>(g_x1 + ((size_t)tt * N_ + n0) * C_)[ch * 72 + off] = a;
        }
      }
    }
    return;
  }

  asm volatile("setmaxnreg.inc.sync.aligned.u32 232;");
  const int wg = warp >> 2, t = tid & 127, wl = warp & 3;
  const int n0 = (bid * 2 + wg) * 9;
  const uint32_t sHt = sH + wg * TILE_BYTES;
  PROF(1, wg, 0);
  uint8_t* pHt = sptr + 2 * W_BYTES + wg * TILE_BYTES;
  {
    const uint8_t* pX = sptr + W_BYTES + wg * TILE_BYTES;
    const int l8 = lane & 7;
    mbar_wait(bars + 48 + 8 * wg, 0);
    uint4 v[4][3];
#pragma unroll
    for (int it = 0; it < 4; ++it) {
      const int row = wl * 16 + it * 4 + (lane >> 3);
      const int j = row / 7, tt = row - j * 7;
#pragma unroll
      for (int c = 0; c < 3; ++c)
        v[it][c] = (row < 63) ? *reinterpret_cast<const uint4*>(pX + tt * FS + j * 384 + (l8 + 8 * c) * 16) : make_uint4(0, 0, 0, 0);
    }
    __syncwarp();
    if (lane == 0) mbar_arrive(bars + 64);
#pragma unroll
    for (int it = 0; it < 4; ++it) {
      const int row = wl * 16 + it * 4 + (lane >> 3);
      float f[24];
#pragma unroll
      for (int c = 0; c < 3; ++c) {
        f[8 * c] = bf_lo(v[it][c].x); f[8 * c + 1] = bf_hi(v[it][c].x); f[8 * c + 2] = bf_lo(v[it][c].y); f[8 * c + 3] = bf_hi(v[it][c].y);
        f[8 * c + 4] = bf_lo(v[it][c].z); f[8 * c + 5] = bf_hi(v[it][c].z); f[8 * c + 6] = bf_lo(v[it][c].w); f[8 * c + 7] = bf_hi(v[it][c].w);
      }
      float s = 0.f;
#pragma unroll
      for (int e = 0; e < 24; ++e) s += f[e];
      s += __shfl_xor_sync(0xffffffffu, s, 1); s += __shfl_xor_sync(0xffffffffu, s, 2); s += __shfl_xor_sync(0xffffffffu, s, 4);
      const float mean = s * (1.f / 192.f);
      float ss = 0.f;
#pragma unroll
      for (int e = 0; e < 24; ++e) { f[e] -= mean; ss += f[e] * f[e]; }
      ss += __shfl_xor_sync(0xffffffffu, ss, 1); ss += __shfl_xor_sync(0xffffffffu, ss, 2); ss += __shfl_xor_sync(0xffffffffu, ss, 4);
      const float rstd = 1.f / sqrtf(ss * (1.f / 192.f) + 1e-5f);
#pragma unroll
      for (int c = 0; c < 3; ++c)
        *reinterpret_cast<uint4*>(pHt + c * 8192 + row * 128 + (((l8 ^ row) & 7) << 4)) =
            make_uint4(pack_bf16(f[8 * c] * rstd, f[8 * c + 1] * rstd), pack_bf16(f[8 * c + 2] * rstd, f[8 * c + 3] * rstd),
                       pack_bf16(f[8 * c + 4] * rstd, f[8 * c + 5] * rstd), pack_bf16(f[8 * c + 6] * rstd, f[8 * c + 7] * rstd));
    }
  }
  PROF(1, wg, 1);
  fence_async_smem();
  named_bar(1 + wg, 128);

  const int g = lane >> 2, q = lane & 3;
  const int r0 = wl * 16 + g, r1 = r0 + 8;
  float acc[96];
  uint32_t af[48];
  mbar_wait(bars, 0);
  if (wg == 1) named_bar(7, 256);
  PROF(1, wg, 2);
  wg_fence();
#pragma unroll
  for (int kk = 0; kk < 12; ++kk) {
    if (kk == 4) mbar_wait(bars + 72, 0);
    if (kk == 8) mbar_wait(bars + 80, 0);
    wgmma_ss_n192<0, 0>(acc, make_desc(sHt + (kk >> 2) * 8192 + (kk & 3) * 32, 16, 1024), make_desc(sWA + (kk >> 2) * WCH + (kk & 3) * 32, 16, 1024), kk > 0);
  }
  wg_commit();
  wg_wait<0>();
  fence_regs(acc);
  PROF(1, wg, 3);
  if (wg == 0) named_arrive(7, 256);
  if (lane == 0) mbar_arrive(bars + 24);
#pragma unroll
  for (int i = 0; i < 48; ++i) af[i] = pack_bf16(acc[2 * i], acc[2 * i + 1]);
  float sc[32];
  wg_fence();
#pragma unroll
  for (int kk = 0; kk < 12; ++kk)
    wgmma_rs_n64<0>(sc, af[4 * kk], af[4 * kk + 1], af[4 * kk + 2], af[4 * kk + 3],
                    make_desc(sHt + (kk >> 2) * 8192 + (kk & 3) * 32, 16, 1024), kk > 0);
  wg_commit();
  wg_wait<0>();
  fence_regs(sc);
  PROF(1, wg, 4);
  uint32_t pf[16];
  {
    const int g0 = r0 / 7, g1 = r1 / 7;
    float mx0 = -INFINITY, mx1 = -INFINITY;
#pragma unroll
    for (int j = 0; j < 8; ++j) {
#pragma unroll
      for (int e = 0; e < 2; ++e) {
        const int col = 8 * j + 2 * q + e;
        const int cg = col / 7;
        if (cg != g0) sc[4 * j + e] = -INFINITY;
        if (cg != g1) sc[4 * j + 2 + e] = -INFINITY;
        mx0 = fmaxf(mx0, sc[4 * j + e]);
        mx1 = fmaxf(mx1, sc[4 * j + 2 + e]);
      }
    }
    mx0 = fmaxf(mx0, __shfl_xor_sync(0xffffffffu, mx0, 1)); mx0 = fmaxf(mx0, __shfl_xor_sync(0xffffffffu, mx0, 2));
    mx1 = fmaxf(mx1, __shfl_xor_sync(0xffffffffu, mx1, 1)); mx1 = fmaxf(mx1, __shfl_xor_sync(0xffffffffu, mx1, 2));
    float l0 = 0.f, l1 = 0.f;
#pragma unroll
    for (int j = 0; j < 8; ++j) {
#pragma unroll
      for (int e = 0; e < 2; ++e) {
        sc[4 * j + e] = ex2((sc[4 * j + e] - mx0) * SM_SCALE_LOG2);
        sc[4 * j + 2 + e] = ex2((sc[4 * j + 2 + e] - mx1) * SM_SCALE_LOG2);
        l0 += sc[4 * j + e];
        l1 += sc[4 * j + 2 + e];
      }
    }
    l0 += __shfl_xor_sync(0xffffffffu, l0, 1); l0 += __shfl_xor_sync(0xffffffffu, l0, 2);
    l1 += __shfl_xor_sync(0xffffffffu, l1, 1); l1 += __shfl_xor_sync(0xffffffffu, l1, 2);
    const float i0 = 1.f / l0, i1 = 1.f / l1;
#pragma unroll
    for (int j = 0; j < 8; ++j) {
      pf[2 * j] = pack_bf16(sc[4 * j] * i0, sc[4 * j + 1] * i0);
      pf[2 * j + 1] = pack_bf16(sc[4 * j + 2] * i1, sc[4 * j + 3] * i1);
    }
  }
  wg_fence();
#pragma unroll
  for (int kk = 0; kk < 4; ++kk)
    wgmma_rs_n192<1>(acc, pf[4 * kk], pf[4 * kk + 1], pf[4 * kk + 2], pf[4 * kk + 3], make_desc(sHt + kk * 2048, 8192, 1024), kk > 0);
  wg_commit();
  wg_wait<0>();
  fence_regs(acc);
#pragma unroll
  for (int i = 0; i < 48; ++i) af[i] = pack_bf16(acc[2 * i], acc[2 * i + 1]);
  PROF(1, wg, 5);
  named_bar(1 + wg, 128);
  if (lane == 0) {
    mbar_expect_tx(bars + 32 + 8 * wg, (wl == 3 ? 1 : 2) * 3456);
#pragma unroll 1
    for (int tt = wl; tt < 7; tt += 4) bulk_g2s(sHt + tt * FS, x + ((size_t)tt * N_ + n0) * C_, 3456, bars + 32 + 8 * wg);
  }
  mbar_wait(bars + 8, 0);
  PROF(1, wg, 6);
  gemm_rs_w(acc, af, sWB, sWB + WCH, sWB + 2 * WCH);
  uint32_t xr[48];
  {
    const int j0 = r0 / 7, t0 = r0 - j0 * 7, j1 = min(r1, 62) / 7, t1 = min(r1, 62) - j1 * 7;
    const uint8_t* p0 = pHt + t0 * FS + j0 * 384 + q * 4;
    const uint8_t* p1 = pHt + t1 * FS + j1 * 384 + q * 4;
    mbar_wait(bars + 32 + 8 * wg, 0);
#pragma unroll
    for (int j = 0; j < 24; ++j) { xr[2 * j] = *reinterpret_cast<const uint32_t*>(p0 + 16 * j); xr[2 * j + 1] = *reinterpret_cast<const uint32_t*>(p1 + 16 * j); }
  }
  wg_wait<0>();
  fence_regs(acc);
  PROF(1, wg, 7);
  named_arrive(8 + wg, 256);
  {
    float s0 = 0.f, s1 = 0.f;
#pragma unroll
    for (int j = 0; j < 24; ++j) {
      const uint32_t a = pack_bf16(bf_lo(xr[2 * j]) + acc[4 * j], bf_hi(xr[2 * j]) + acc[4 * j + 1]);
      const uint32_t b = pack_bf16(bf_lo(xr[2 * j + 1]) + acc[4 * j + 2], bf_hi(xr[2 * j + 1]) + acc[4 * j + 3]);
      xr[2 * j] = a; xr[2 * j + 1] = b;
      acc[4 * j] = bf_lo(a); acc[4 * j + 1] = bf_hi(a); acc[4 * j + 2] = bf_lo(b); acc[4 * j + 3] = bf_hi(b);
      s0 += acc[4 * j] + acc[4 * j + 1];
      s1 += acc[4 * j + 2] + acc[4 * j + 3];
    }
    s0 += __shfl_xor_sync(0xffffffffu, s0, 1); s0 += __shfl_xor_sync(0xffffffffu, s0, 2);
    s1 += __shfl_xor_sync(0xffffffffu, s1, 1); s1 += __shfl_xor_sync(0xffffffffu, s1, 2);
    const float mean0 = s0 * (1.f / 192.f), mean1 = s1 * (1.f / 192.f);
    float q0 = 0.f, q1 = 0.f;
#pragma unroll
    for (int j = 0; j < 24; ++j) {
      acc[4 * j] -= mean0; acc[4 * j + 1] -= mean0; acc[4 * j + 2] -= mean1; acc[4 * j + 3] -= mean1;
      q0 += acc[4 * j] * acc[4 * j] + acc[4 * j + 1] * acc[4 * j + 1];
      q1 += acc[4 * j + 2] * acc[4 * j + 2] + acc[4 * j + 3] * acc[4 * j + 3];
    }
    q0 += __shfl_xor_sync(0xffffffffu, q0, 1); q0 += __shfl_xor_sync(0xffffffffu, q0, 2);
    q1 += __shfl_xor_sync(0xffffffffu, q1, 1); q1 += __shfl_xor_sync(0xffffffffu, q1, 2);
    const float rs0 = 1.f / sqrtf(q0 * (1.f / 192.f) + 1e-5f), rs1 = 1.f / sqrtf(q1 * (1.f / 192.f) + 1e-5f);
#pragma unroll
    for (int j = 0; j < 24; ++j) {
      af[2 * j] = pack_bf16(acc[4 * j] * rs0, acc[4 * j + 1] * rs0);
      af[2 * j + 1] = pack_bf16(acc[4 * j + 2] * rs1, acc[4 * j + 3] * rs1);
    }
  }
  PROF(1, wg, 8);
  const int lrow = wl * 16 + ((lane >> 3) & 1) * 8 + (lane & 7), uh = lane >> 4;
  const int lj = lrow / 7, lt = lrow - lj * 7;
  const bool lvalid = lrow < 63;
  const uint32_t offX = lvalid ? (uint32_t)(lt * FS + lj * 384 + uh * 16) : 3456u;
  const uint32_t offH = lvalid ? (uint32_t)(lt * FS + lj * 128) : 3456u;
  const int lph = (n0 + lj) & 7;
  const uint32_t sStH = wg ? (sWB + TILE_BYTES) : sX;
  PROF(1, wg, 12);
  if (wg == 1) named_bar(8, 256);
  named_bar(1 + wg, 128);
  PROF(1, wg, 13);
#pragma unroll
  for (int i = 0; i < 12; ++i) {
    stsm_x4(sHt + offX + (lvalid ? i * 32 : 0), xr[4 * i], xr[4 * i + 1], xr[4 * i + 2], xr[4 * i + 3]);
    const int u = 2 * i + uh;
    stsm_x4(sStH + offH + (lvalid ? (uint32_t)((u >> 3) * 1152 + (((u ^ lph) & 7) << 4)) : 0u), af[4 * i], af[4 * i + 1], af[4 * i + 2], af[4 * i + 3]);
  }
  PROF(1, wg, 14);
  named_arrive(6 + 4 * wg, 256);
  mbar_wait(bars + 16, 0);
  PROF(1, wg, 9);
  gemm_rs_w(acc, af, sWA, sWA + WCH, sWA + 2 * WCH);
  PROF(1, wg, 16);
  wg_wait<0>();
  fence_regs(acc);
  PROF(1, wg, 10);
#pragma unroll
  for (int i = 0; i < 48; ++i) af[i] = pack_bf16(acc[2 * i], acc[2 * i + 1]);
  if (wg == 0) named_bar(9, 256);
  const uint32_t sStQ = sWB + (wg ? 0 : 2 * TILE_BYTES);
#pragma unroll
  for (int i = 0; i < 12; ++i) {
    const int u = 2 * i + uh;
    stsm_x4(sStQ + offH + (lvalid ? (uint32_t)((u >> 3) * 1152 + (((u ^ lph) & 7) << 4)) : 0u), af[4 * i], af[4 * i + 1], af[4 * i + 2], af[4 * i + 3]);
  }
  named_bar(1 + wg, 128);
#pragma unroll 4
  for (int it = 0; it < 12; ++it) {
    const int idx = it * 128 + t;
    if (idx < 1512) {
      const int i = idx / 72, off = idx - i * 72, tt = i / 3, ch = i - tt * 3;
      reinterpret_cast<uint4*>(g_q2 + ((size_t)i * N_ + n0) * 64)[off] = *reinterpret_cast<const uint4*>(sptr + (sStQ - sbase) + tt * FS + ch * 1152 + off * 16);
    }
  }
  PROF(1, wg, 11);
}

constexpr int KB = 144;
constexpr int KCH = KB * 128;
constexpr int STAGE_BYTES = 3 * KCH;
constexpr int NSTAGE = 3;
constexpr int P2_Q_OFF = NSTAGE * STAGE_BYTES;
constexpr int P2_ML_OFF = P2_Q_OFF + 2 * TILE_BYTES;
constexpr int P2_BAR_OFF = P2_ML_OFF + 2048;
constexpr int P2_SMEM = P2_BAR_OFF + 128 + 1024;

constexpr int OPITCH = 400;
__device__ __forceinline__ uint32_t add_bf2(uint32_t a, uint32_t b) { return pack_bf16(bf_lo(a) + bf_lo(b), bf_hi(a) + bf_hi(b)); }

__global__ void __cluster_dims__(2, 1, 1) __launch_bounds__(384, 1) p2_kernel(__nv_bfloat16* __restrict__ out) {
  extern __shared__ uint8_t smem_raw[];
  const uint32_t sbase = (smem_u32(smem_raw) + 1023) & ~1023u;
  uint8_t* sptr = smem_raw + (sbase - smem_u32(smem_raw));
  const uint32_t sQ = sbase + P2_Q_OFF, sML = sbase + P2_ML_OFF, bars = sbase + P2_BAR_OFF;
  const uint32_t bFull = bars, bEmpty = bars + 24, bQ0 = bars + 48, bQ1 = bars + 64, bW = bars + 80, bXFree = bars + 88, bXFull = bars + 96, bQ0Free = bars + 104;
  const int tid = threadIdx.x, lane = tid & 31;
  const int warp = __shfl_sync(0xffffffffu, tid >> 5, 0);
  const int cl = blockIdx.x >> 1, rank = blockIdx.x & 1;
  if (tid == 0) PROF(2, 3, 0);
  if (tid == 0) {
    for (int i = 0; i < NSTAGE; ++i) { mbar_init(bFull + 8 * i, 1); mbar_init(bEmpty + 8 * i, 8); }
    for (int i = 0; i < 2; ++i) { mbar_init(bQ0 + 8 * i, 1); mbar_init(bQ1 + 8 * i, 1); }
    mbar_init(bQ0Free, rank ? 8 : 4);
    mbar_init(bW, 1); mbar_init(bXFree, 8); mbar_init(bXFull, 1);
    mbar_expect_tx(bXFull, 13 * 128 * 16);
    fence_mbar_init();
  }
  const int f = cl / 9, c = cl - f * 9;
  const int nmain = 5 - rank;
  const int ntot = nmain + 1;
  const uint32_t sW0 = sbase + (ntot % NSTAGE) * STAGE_BYTES, sW1 = sW0 + WCH, sW2 = sbase + ((ntot + 1) % NSTAGE) * STAGE_BYTES;
  cluster_sync_all();
  pdl_wait();
  if (blockIdx.x == 0 && tid < 4) g_cnt[16 + tid] = 0;

  if (warp >= 8) {
    asm volatile("setmaxnreg.dec.sync.aligned.u32 40;");
    if (warp == 8 && lane == 0) {
      const __nv_bfloat16* kv = g_h2 + (size_t)(f * 3) * (N_ * 64);
#pragma unroll 1
      for (int i = 0; i < ntot; ++i) {
        const int blk = (i == 0) ? c : (rank * 5 + i - 1);
        const int st = i % NSTAGE;
        if (i >= NSTAGE) mbar_wait(bEmpty + 8 * st, ((i / NSTAGE) - 1) & 1);
        if (i == 2) mbar_wait(bQ0Free, 0);
        mbar_expect_tx(bFull + 8 * st, STAGE_BYTES);
#pragma unroll
        for (int ch = 0; ch < 3; ++ch) bulk_g2s(sbase + st * STAGE_BYTES + ch * KCH, kv + (size_t)ch * (N_ * 64) + (size_t)blk * KB * 64, KCH, bFull + 8 * st);
      }
      const __nv_bfloat16* wsrc = g_w + 3 * 3 * 192 * 64;
      mbar_expect_tx(bW, W_BYTES);
      mbar_wait(bEmpty + 8 * (ntot % NSTAGE), ((ntot / NSTAGE) - 1) & 1);
      bulk_g2s(sW0, wsrc, 2 * WCH, bW);
      mbar_wait(bEmpty + 8 * ((ntot + 1) % NSTAGE), (((ntot + 1) / NSTAGE) - 1) & 1);
      bulk_g2s(sW2, wsrc + 2 * 192 * 64, WCH, bW);
    } else if (warp == 9 && lane == 0) {
      const __nv_bfloat16* qsrc = g_q2 + (size_t)(f * 3) * (N_ * 64);
#pragma unroll 1
      for (int i = 0; i < 4; ++i) {
        const int sg = i >> 1, w = i & 1;
        if (sg == 0 && rank == 0 && w == 1) continue;
        if (i == 2) mbar_wait(bFull, 0);
        const int qr = sg ? (128 * c + 64 * w) : (rank ? 1152 + 64 * w : 1280);
        const uint32_t bar = (sg ? bQ1 : bQ0) + 8 * w, dst = (sg ? sQ : sbase + 2 * STAGE_BYTES) + w * TILE_BYTES;
        mbar_expect_tx(bar, TILE_BYTES);
#pragma unroll
        for (int ch = 0; ch < 3; ++ch) bulk_g2s(dst + ch * 8192, qsrc + (size_t)ch * (N_ * 64) + (size_t)qr * 64, 8192, bar);
      }
    }
    if (warp >= 10 && (rank || warp == 10)) {
      named_bar(6 + warp - 10, 160);
      if (lane == 0) { __threadfence(); atomicAdd(g_cnt + f, 1u); }
    }
    return;
  }

  asm volatile("setmaxnreg.inc.sync.aligned.u32 232;");
  const int w = warp >> 2, wl = warp & 3, t = tid & 127;
  const int g = lane >> 2, q = lane & 3;
  const int r0 = wl * 16 + g;
  const uint32_t sQt = sQ + w * TILE_BYTES;
  PROF(2, w, 0);
  float o[96];
  float m0, m1, l0, l1;
  {
    const int nrel = w ? ntot : (ntot + rank);
    int phase = 0;
    if (w == 1) named_arrive(4, 256);
    auto acquire = [&]() { named_bar(4 + w, 256); };
    auto release = [&]() { ++phase; if (phase <= nrel) named_arrive(4 + (w ^ 1), 256); };
    const bool skip0 = (rank == 0 && w == 1);
    int k = 0;
    uint32_t pf[36];
    uint32_t sK, bE;
    float sc[72];
    auto next_stage = [&]() {
      const int st = k % NSTAGE;
      sK = sbase + st * STAGE_BYTES; bE = bEmpty + 8 * st;
      mbar_wait(bFull + 8 * st, (k / NSTAGE) & 1);
      PROF(2, w, 2 + 3 * k);
    };
    auto issue_s = [&](uint32_t dQ) {
      const uint32_t dK = make_desc(sK, 16, 1024);
#pragma unroll
      for (int kk = 0; kk < 12; ++kk)
        wgmma_ss_n144<0, 0>(sc, dQ + ((kk >> 2) * 512 + (kk & 3) * 2), dK + ((kk >> 2) * (KCH / 16) + (kk & 3) * 2), kk > 0);
      wg_commit();
    };
    auto issue_pv = [&](uint32_t sV, int acc) {
      const uint32_t dV = make_desc(sV, KCH, 1024);
#pragma unroll
      for (int kk = 0; kk < 9; ++kk)
        wgmma_rs_n192<1>(o, pf[4 * kk], pf[4 * kk + 1], pf[4 * kk + 2], pf[4 * kk + 3], dV + kk * 128, acc || (kk > 0));
      wg_commit();
    };
    float a0, a1;
    auto softmax = [&]() {
      float mx0 = sc[0], mx1 = sc[2];
#pragma unroll
      for (int j = 0; j < 18; ++j) {
        mx0 = fmaxf(mx0, fmaxf(sc[4 * j], sc[4 * j + 1]));
        mx1 = fmaxf(mx1, fmaxf(sc[4 * j + 2], sc[4 * j + 3]));
      }
      mx0 = fmaxf(mx0, __shfl_xor_sync(0xffffffffu, mx0, 1)); mx0 = fmaxf(mx0, __shfl_xor_sync(0xffffffffu, mx0, 2));
      mx1 = fmaxf(mx1, __shfl_xor_sync(0xffffffffu, mx1, 1)); mx1 = fmaxf(mx1, __shfl_xor_sync(0xffffffffu, mx1, 2));
      const float mn0 = fmaxf(m0, mx0), mn1 = fmaxf(m1, mx1);
      a0 = ex2((m0 - mn0) * SM_SCALE_LOG2); a1 = ex2((m1 - mn1) * SM_SCALE_LOG2);
      m0 = mn0; m1 = mn1;
      const float ms0 = mn0 * SM_SCALE_LOG2, ms1 = mn1 * SM_SCALE_LOG2;
      float ls0 = 0.f, ls1 = 0.f;
#pragma unroll
      for (int j = 0; j < 18; ++j) {
        sc[4 * j] = ex2(fmaf(sc[4 * j], SM_SCALE_LOG2, -ms0)); sc[4 * j + 1] = ex2(fmaf(sc[4 * j + 1], SM_SCALE_LOG2, -ms0));
        sc[4 * j + 2] = ex2(fmaf(sc[4 * j + 2], SM_SCALE_LOG2, -ms1)); sc[4 * j + 3] = ex2(fmaf(sc[4 * j + 3], SM_SCALE_LOG2, -ms1));
        ls0 += sc[4 * j] + sc[4 * j + 1]; ls1 += sc[4 * j + 2] + sc[4 * j + 3];
      }
      l0 = l0 * a0 + ls0; l1 = l1 * a1 + ls1;
    };
    const uint32_t dQ1 = make_desc(sQt, 16, 1024);
    m0 = m1 = -INFINITY; l0 = l1 = 0.f;
    if (skip0) {
      if (lane == 0) mbar_arrive(bEmpty);
      k = 1;
    }
    mbar_wait((skip0 ? bQ1 : bQ0) + 8 * w, 0);
    PROF(2, w, 1);
    next_stage();
    acquire();
    wg_fence();
    issue_s(skip0 ? dQ1 : make_desc(sbase + 2 * STAGE_BYTES + w * TILE_BYTES, 16, 1024));
    release();
    wg_wait<0>();
    fence_regs(sc);
    PROF(2, w, 3 + 3 * k);
    if (!skip0 && lane == 0) mbar_arrive(bQ0Free);
    softmax();
#pragma unroll
    for (int j = 0; j < 36; ++j) pf[j] = pack_bf16(sc[2 * j], sc[2 * j + 1]);
    ++k;
    mbar_wait(bQ1 + 8 * w, 0);
#pragma unroll 1
    for (; k < ntot; ++k) {
      const uint32_t sV = sK, bEv = bE;
      next_stage();
      acquire();
      wg_fence();
      issue_s(dQ1);
      issue_pv(sV, k > 2);
      release();
      float4 ml0;
      if (k == 1) {
        ml0 = make_float4(m0, m1, l0, l1);
        m0 = m1 = -INFINITY; l0 = l1 = 0.f;
      }
      wg_wait<1>();
      fence_regs(sc);
      PROF(2, w, 3 + 3 * k);
      if (k == ntot - 1 && lane == 0) mbar_arrive_remote(mapa(bXFree, rank ^ 1));
      softmax();
      wg_wait<0>();
      fence_regs(o);
      if (lane == 0) mbar_arrive(bEv);
      if (k == 1) {
        ml0.z += __shfl_xor_sync(0xffffffffu, ml0.z, 1); ml0.z += __shfl_xor_sync(0xffffffffu, ml0.z, 2);
        ml0.w += __shfl_xor_sync(0xffffffffu, ml0.w, 1); ml0.w += __shfl_xor_sync(0xffffffffu, ml0.w, 2);
        const int slot = cl * 3 + (rank ? w : 2);
        if (rank || wl == 0) {
          uint4* po = g_part + (size_t)slot * (12 * 128) + t;
#pragma unroll
          for (int j = 0; j < 12; ++j)
            po[j * 128] = make_uint4(pack_bf16(o[8 * j], o[8 * j + 1]), pack_bf16(o[8 * j + 2], o[8 * j + 3]), pack_bf16(o[8 * j + 4], o[8 * j + 5]), pack_bf16(o[8 * j + 6], o[8 * j + 7]));
          g_pml[slot * 128 + t] = ml0;
        }
        named_arrive(6 + w, 160);
      } else {
#pragma unroll
        for (int j = 0; j < 24; ++j) { o[4 * j] *= a0; o[4 * j + 1] *= a0; o[4 * j + 2] *= a1; o[4 * j + 3] *= a1; }
      }
#pragma unroll
      for (int j = 0; j < 36; ++j) pf[j] = pack_bf16(sc[2 * j], sc[2 * j + 1]);
    }
    acquire();
    wg_fence();
    issue_pv(sK, 1);
    release();
    wg_wait<0>();
    fence_regs(o);
    if (lane == 0) mbar_arrive(bE);
    PROF(2, w, 1 + 3 * k);
    l0 += __shfl_xor_sync(0xffffffffu, l0, 1); l0 += __shfl_xor_sync(0xffffffffu, l0, 2);
    l1 += __shfl_xor_sync(0xffffffffu, l1, 1); l1 += __shfl_xor_sync(0xffffffffu, l1, 2);
    PROF(2, w, 20);
    if (w != rank) {
      mbar_wait_cluster(bXFree, 0);
      const uint32_t rq = mapa(sQ, rank ^ 1) + t * 16, rb = mapa(bXFull, rank ^ 1);
#pragma unroll
      for (int i = 0; i < 12; ++i)
        st_async_v4(rq + i * 2048, __uint_as_float(pack_bf16(o[8 * i], o[8 * i + 1])), __uint_as_float(pack_bf16(o[8 * i + 2], o[8 * i + 3])),
                    __uint_as_float(pack_bf16(o[8 * i + 4], o[8 * i + 5])), __uint_as_float(pack_bf16(o[8 * i + 6], o[8 * i + 7])), rb);
      st_async_v4(mapa(sML, rank ^ 1) + t * 16, m0, m1, l0, l1, rb);
      PROF(2, w, 21);
      if (rank == 0) return;
    }
  }

  const bool recv = (w == rank);
  mbar_wait(bW, 0);
  const uint32_t sT = sW2 + WCH;
  const int grow = f * N_ + (recv ? (128 * c + 64 * w) : (1152 + 16 * c));
  uint32_t af[48];
  if (recv) {
    mbar_wait_cluster(bXFull, 0);
    PROF(2, w, 17);
    const float4 ml = *reinterpret_cast<const float4*>(sptr + P2_ML_OFF + t * 16);
    const float mn0 = fmaxf(m0, ml.x), mn1 = fmaxf(m1, ml.y);
    float a0 = ex2((m0 - mn0) * SM_SCALE_LOG2), a1 = ex2((m1 - mn1) * SM_SCALE_LOG2);
    float b0 = ex2((ml.x - mn0) * SM_SCALE_LOG2), b1 = ex2((ml.y - mn1) * SM_SCALE_LOG2);
    const float i0 = 1.f / (a0 * l0 + b0 * ml.z), i1 = 1.f / (a1 * l1 + b1 * ml.w);
    a0 *= i0; b0 *= i0; a1 *= i1; b1 *= i1;
#pragma unroll
    for (int i = 0; i < 12; ++i) {
      const uint4 v = *reinterpret_cast<const uint4*>(sptr + P2_Q_OFF + i * 2048 + t * 16);
      af[4 * i] = pack_bf16(a0 * o[8 * i] + b0 * bf_lo(v.x), a0 * o[8 * i + 1] + b0 * bf_hi(v.x));
      af[4 * i + 1] = pack_bf16(a1 * o[8 * i + 2] + b1 * bf_lo(v.y), a1 * o[8 * i + 3] + b1 * bf_hi(v.y));
      af[4 * i + 2] = pack_bf16(a0 * o[8 * i + 4] + b0 * bf_lo(v.z), a0 * o[8 * i + 5] + b0 * bf_hi(v.z));
      af[4 * i + 3] = pack_bf16(a1 * o[8 * i + 6] + b1 * bf_lo(v.w), a1 * o[8 * i + 7] + b1 * bf_hi(v.w));
    }
  } else {
    if (t == 0) wait_counter(g_cnt + f, 27);
    named_bar(1 + w, 128);
    const int slot0 = f * 27 + (c >> 2), tl = (c & 3) * 32 + lane;
    float4 mlv[9]; uint4 v[9][3];
#pragma unroll
    for (int i = 0; i < 9; ++i) {
      mlv[i] = __ldcg(g_pml + (slot0 + 3 * i) * 128 + tl);
#pragma unroll
      for (int j = 0; j < 3; ++j) v[i][j] = __ldcg(g_part + (size_t)(slot0 + 3 * i) * (12 * 128) + (wl * 3 + j) * 128 + tl);
    }
    float mn0 = mlv[0].x, mn1 = mlv[0].y;
#pragma unroll
    for (int i = 1; i < 9; ++i) { mn0 = fmaxf(mn0, mlv[i].x); mn1 = fmaxf(mn1, mlv[i].y); }
    float s0 = 0.f, s1 = 0.f;
#pragma unroll
    for (int i = 0; i < 9; ++i) {
      mlv[i].x = ex2((mlv[i].x - mn0) * SM_SCALE_LOG2); mlv[i].y = ex2((mlv[i].y - mn1) * SM_SCALE_LOG2);
      s0 += mlv[i].x * mlv[i].z; s1 += mlv[i].y * mlv[i].w;
    }
    s0 = 1.f / s0; s1 = 1.f / s1;
    uint8_t* pT = sptr + (sT - sbase);
#pragma unroll
    for (int j = 0; j < 3; ++j) {
      float x[8] = {};
#pragma unroll
      for (int i = 0; i < 9; ++i) {
        x[0] += mlv[i].x * bf_lo(v[i][j].x); x[1] += mlv[i].x * bf_hi(v[i][j].x); x[2] += mlv[i].y * bf_lo(v[i][j].y); x[3] += mlv[i].y * bf_hi(v[i][j].y);
        x[4] += mlv[i].x * bf_lo(v[i][j].z); x[5] += mlv[i].x * bf_hi(v[i][j].z); x[6] += mlv[i].y * bf_lo(v[i][j].w); x[7] += mlv[i].y * bf_hi(v[i][j].w);
      }
      const int col = (wl * 3 + j) * 16 + 2 * q;
      *reinterpret_cast<uint32_t*>(pT + g * OPITCH + col * 2) = pack_bf16(x[0] * s0, x[1] * s0);
      *reinterpret_cast<uint32_t*>(pT + (g + 8) * OPITCH + col * 2) = pack_bf16(x[2] * s1, x[3] * s1);
      *reinterpret_cast<uint32_t*>(pT + g * OPITCH + col * 2 + 16) = pack_bf16(x[4] * s0, x[5] * s0);
      *reinterpret_cast<uint32_t*>(pT + (g + 8) * OPITCH + col * 2 + 16) = pack_bf16(x[6] * s1, x[7] * s1);
    }
    named_bar(1 + w, 128);
#pragma unroll
    for (int j = 0; j < 24; ++j) {
      af[2 * j] = *reinterpret_cast<const uint32_t*>(pT + g * OPITCH + j * 16 + q * 4);
      af[2 * j + 1] = *reinterpret_cast<const uint32_t*>(pT + (g + 8) * OPITCH + j * 16 + q * 4);
    }
  }
  PROF(2, w, 18);
  gemm_rs_w(o, af, sW0, sW1, sW2);
  const int nit = recv ? 12 : 3;
  uint4 xv[12];
  {
    const uint4* src = reinterpret_cast<const uint4*>(g_x1 + (size_t)grow * C_) + t;
#pragma unroll
    for (int it = 0; it < 12; ++it) if (it < nit) xv[it] = __ldcg(src + it * 128);
  }
  named_bar(1 + w, 128);
  wg_wait<0>();
  fence_regs(o);
  PROF(2, w, 22);
  const uint32_t sS = recv ? sQ : sT;
  if (recv || wl == 0) {
    const uint32_t addr = sS + (wl * 16 + ((lane >> 3) & 1) * 8 + (lane & 7)) * OPITCH + (lane >> 4) * 16;
#pragma unroll
    for (int i = 0; i < 12; ++i)
      stsm_x4(addr + i * 32, pack_bf16(o[8 * i], o[8 * i + 1]), pack_bf16(o[8 * i + 2], o[8 * i + 3]),
              pack_bf16(o[8 * i + 4], o[8 * i + 5]), pack_bf16(o[8 * i + 6], o[8 * i + 7]));
  }
  named_bar(1 + w, 128);
  {
    const uint8_t* pS = sptr + (sS - sbase);
    uint4* dst = reinterpret_cast<uint4*>(out + (size_t)grow * C_);
#pragma unroll
    for (int it = 0; it < 12; ++it) {
      if (it < nit) {
        const int unit = it * 128 + t, row = unit / 24, u = unit - row * 24;
        const uint4 y = *reinterpret_cast<const uint4*>(pS + row * OPITCH + u * 16);
        dst[unit] = make_uint4(add_bf2(xv[it].x, y.x), add_bf2(xv[it].y, y.y), add_bf2(xv[it].z, y.z), add_bf2(xv[it].w, y.w));
      }
    }
  }
  PROF(2, w, 23);
}

}

extern "C" void kernel_launch(void* const* d_in, const int* in_sizes, int n_in, void* d_out, int out_size) {
  using namespace tsf;
  const __nv_bfloat16* x = (const __nv_bfloat16*)d_in[0];
  const __nv_bfloat16* wqkv_t = (const __nv_bfloat16*)d_in[1];
  const __nv_bfloat16* wo_t = (const __nv_bfloat16*)d_in[2];
  const __nv_bfloat16* wqkv_s = (const __nv_bfloat16*)d_in[3];
  const __nv_bfloat16* wo_s = (const __nv_bfloat16*)d_in[4];
  __nv_bfloat16* out = (__nv_bfloat16*)d_out;
  static bool init = false;
  if (!init) {
    cudaFuncSetAttribute(p1_kernel, cudaFuncAttributeMaxDynamicSharedMemorySize, P1_SMEM);
    cudaFuncSetAttribute(p2_kernel, cudaFuncAttributeMaxDynamicSharedMemorySize, P2_SMEM);
    cudaFuncSetAttribute(p1_kernel, cudaFuncAttributePreferredSharedMemoryCarveout, cudaSharedmemCarveoutMaxShared);
    cudaFuncSetAttribute(p2_kernel, cudaFuncAttributePreferredSharedMemoryCarveout, cudaSharedmemCarveoutMaxShared);
    init = true;
  }
  cudaStream_t st = cudaStreamPerThread;
  p1_kernel<<<120, 384, P1_SMEM, st>>>(x, wqkv_t, wo_t, wqkv_s, wo_s);
  cudaLaunchAttribute at[1];
  at[0].id = cudaLaunchAttributeProgrammaticStreamSerialization;
  at[0].val.programmaticStreamSerializationAllowed = 1;
  {
    cudaLaunchConfig_t cfg = {};
    cfg.gridDim = dim3(126); cfg.blockDim = dim3(384); cfg.dynamicSmemBytes = P2_SMEM; cfg.stream = st;
    cfg.attrs = at; cfg.numAttrs = 1;
    cudaLaunchKernelEx(&cfg, p2_kernel, out);
  }
}
```

```cpp
#include <cuda_runtime.h>
#include <cuda_bf16.h>
#include <stdint.h>

namespace tsf {

constexpr int T_ = 7, N_ = 1296, C_ = 192, ROWS = T_ * N_;
constexpr float SM_SCALE_LOG2 = 0.07216878364870322f * 1.4426950408889634f;
constexpr uint32_t SPIN_LIMIT = 1u << 24;

__device__ __align__(1024) __nv_bfloat16 g_w[4 * 3 * 192 * 64];
__device__ __align__(1024) __nv_bfloat16 g_x1[ROWS * C_];
__device__ __align__(1024) __nv_bfloat16 g_h2[T_ * 3 * N_ * 64];
__device__ __align__(1024) __nv_bfloat16 g_q2[T_ * 3 * N_ * 64 + 64 * 64];
__device__ __align__(1024) uint4 g_part[189 * 12 * 128];
__device__ float4 g_pml[189 * 128];
__device__ unsigned int g_cnt[24];

#define PROF(kern, slot, idx)
__device__ __forceinline__ uint32_t smem_u32(const void* p) { return (uint32_t)__cvta_generic_to_shared(p); }
__device__ __forceinline__ void mbar_init(uint32_t bar, uint32_t count) {
  asm volatile("mbarrier.init.shared::cta.b64 [%0], %1;" ::"r"(bar), "r"(count) : "memory");
}
__device__ __forceinline__ void mbar_expect_tx(uint32_t bar, uint32_t bytes) {
  asm volatile("mbarrier.arrive.expect_tx.shared::cta.b64 _, [%0], %1;" ::"r"(bar), "r"(bytes) : "memory");
}
__device__ __forceinline__ void mbar_arrive(uint32_t bar) {
  asm volatile("mbarrier.arrive.shared::cta.b64 _, [%0];" ::"r"(bar) : "memory");
}
__device__ __forceinline__ void mbar_arrive_remote(uint32_t rbar) {
  asm volatile("mbarrier.arrive.release.cluster.shared::cluster.b64 _, [%0];" ::"r"(rbar) : "memory");
}
__device__ __forceinline__ bool mbar_try(uint32_t bar, uint32_t parity) {
  uint32_t ok;
  asm volatile("{\n.reg .pred p;\nmbarrier.try_wait.parity.shared::cta.b64 p, [%1], %2;\nselp.u32 %0, 1, 0, p;\n}\n"
               : "=r"(ok) : "r"(bar), "r"(parity) : "memory");
  return ok != 0;
}
__device__ __forceinline__ bool mbar_try_cluster(uint32_t bar, uint32_t parity) {
  uint32_t ok;
  asm volatile("{\n.reg .pred p;\nmbarrier.try_wait.parity.acquire.cluster.shared::cta.b64 p, [%1], %2;\nselp.u32 %0, 1, 0, p;\n}\n"
               : "=r"(ok) : "r"(bar), "r"(parity) : "memory");
  return ok != 0;
}
__device__ __forceinline__ void mbar_wait(uint32_t bar, uint32_t parity) {
#pragma unroll 1
  for (uint32_t it = 0; it < SPIN_LIMIT; ++it)
    if (mbar_try(bar, parity)) return;
  __trap();
}
__device__ __forceinline__ void mbar_wait_cluster(uint32_t bar, uint32_t parity) {
#pragma unroll 1
  for (uint32_t it = 0; it < SPIN_LIMIT; ++it)
    if (mbar_try_cluster(bar, parity)) return;
  __trap();
}
__device__ __forceinline__ void bulk_g2s(uint32_t dst, const void* src, uint32_t bytes, uint32_t bar) {
  asm volatile("cp.async.bulk.shared::cluster.global.mbarrier::complete_tx::bytes [%0], [%1], %2, [%3];"
               ::"r"(dst), "l"(src), "r"(bytes), "r"(bar) : "memory");
}
__device__ __forceinline__ void fence_async_smem() { asm volatile("fence.proxy.async.shared::cta;" ::: "memory"); }
__device__ __forceinline__ void fence_mbar_init() { asm volatile("fence.mbarrier_init.release.cluster;" ::: "memory"); }
__device__ __forceinline__ void named_bar(int id, int n) { asm volatile("bar.sync %0, %1;" ::"r"(id), "r"(n) : "memory"); }
__device__ __forceinline__ void wg_fence() { asm volatile("wgmma.fence.sync.aligned;" ::: "memory"); }
__device__ __forceinline__ void wg_commit() { asm volatile("wgmma.commit_group.sync.aligned;" ::: "memory"); }
template <int N> __device__ __forceinline__ void wg_wait() { asm volatile("wgmma.wait_group.sync.aligned %0;" ::"n"(N) : "memory"); }
template <int N> __device__ __forceinline__ void fence_regs(float (&d)[N]) {
#pragma unroll
  for (int i = 0; i < N; ++i) asm volatile("" : "+f"(d[i])::"memory");
}
__device__ __forceinline__ void pdl_wait() { asm volatile("griddepcontrol.wait;" ::: "memory"); }
__device__ __forceinline__ void pdl_launch() { asm volatile("griddepcontrol.launch_dependents;" ::: "memory"); }
__device__ __forceinline__ uint32_t mapa(uint32_t addr, uint32_t rank) {
  uint32_t r;
  asm volatile("mapa.shared::cluster.u32 %0, %1, %2;" : "=r"(r) : "r"(addr), "r"(rank));
  return r;
}
__device__ __forceinline__ void cluster_sync_all() {
  asm volatile("barrier.cluster.arrive.release.aligned;\nbarrier.cluster.wait.acquire.aligned;" ::: "memory");
}
__device__ __forceinline__ void st_async_v4(uint32_t addr, float a, float b, float c, float d, uint32_t rbar) {
  asm volatile("st.async.weak.shared::cluster.mbarrier::complete_tx::bytes.v4.f32 [%0], {%1, %2, %3, %4}, [%5];"
               ::"r"(addr), "f"(a), "f"(b), "f"(c), "f"(d), "r"(rbar) : "memory");
}
__device__ __forceinline__ uint32_t make_desc(uint32_t addr, uint32_t lbo, uint32_t) {
  return ((addr & 0x3FFFF) >> 4) | ((lbo >> 4) << 16);
}
__device__ __forceinline__ uint32_t pack_bf16(float lo, float hi) {
  uint32_t r;
  asm("cvt.rn.bf16x2.f32 %0, %1, %2;" : "=r"(r) : "f"(hi), "f"(lo));
  return r;
}
__device__ __forceinline__ float bf_lo(uint32_t v) { return __uint_as_float(v << 16); }
__device__ __forceinline__ float bf_hi(uint32_t v) { return __uint_as_float(v & 0xffff0000u); }
__device__ __forceinline__ float ex2(float x) {
  float r;
  asm("ex2.approx.ftz.f32 %0, %1;" : "=f"(r) : "f"(x));
  return r;
}
__device__ __forceinline__ void stsm_x4(uint32_t addr, uint32_t r0, uint32_t r1, uint32_t r2, uint32_t r3) {
  asm volatile("stmatrix.sync.aligned.m8n8.x4.shared.b16 [%0], {%1, %2, %3, %4};" ::"r"(addr), "r"(r0), "r"(r1), "r"(r2), "r"(r3) : "memory");
}
__device__ __forceinline__ void named_arrive(int id, int n) { asm volatile("bar.arrive %0, %1;" ::"r"(id), "r"(n) : "memory"); }
__device__ __forceinline__ void wait_counter(const unsigned int* p, unsigned int target) {
#pragma unroll 1
  for (uint32_t it = 0; it < SPIN_LIMIT; ++it) {
    unsigned int v;
    asm volatile("ld.acquire.gpu.global.u32 %0, [%1];" : "=r"(v) : "l"(p) : "memory");
    if (v >= target) return;
    __nanosleep(32);
  }
  __trap();
}
__device__ __forceinline__ void fence_async_all() { asm volatile("fence.proxy.async;" ::: "memory"); }
__device__ __forceinline__ int swz(int row, int col) { return row * 64 + ((((col >> 3) ^ row) & 7) << 3) + (col & 7); }

template <int TA, int TB>
__device__ __forceinline__ void wgmma_ss_n48(float (&d)[24], uint32_t da, uint32_t db, int sc) {
  asm volatile("{\n.reg .pred p;\n.reg .b64 da, db;\n.reg .b32 hi;\nmov.b32 hi, 0x40000040;\nmov.b64 da, {%24, hi};\nmov.b64 db, {%25, hi};\nsetp.ne.b32 p, %26, 0;\n"
    "wgmma.mma_async.sync.aligned.m64n48k16.f32.bf16.bf16 "
    "{%0, %1, %2, %3, %4, %5, %6, %7, %8, %9, %10, %11, %12, %13, %14, %15, %16, %17, %18, %19, %20, %21, %22, %23}, "
    "da, db, p, 1, 1, %27, %28;\n}\n"
    : "+f"(d[0]), "+f"(d[1]), "+f"(d[2]), "+f"(d[3]), "+f"(d[4]), "+f"(d[5]), "+f"(d[6]), "+f"(d[7]), "+f"(d[8]), "+f"(d[9]), "+f"(d[10]), "+f"(d[11]), "+f"(d[12]), "+f"(d[13]), "+f"(d[14]), "+f"(d[15]), "+f"(d[16]), "+f"(d[17]), "+f"(d[18]), "+f"(d[19]), "+f"(d[20]), "+f"(d[21]), "+f"(d[22]), "+f"(d[23])
    : "r"(da), "r"(db), "r"(sc), "n"(TA), "n"(TB));
}
template <int TA, int TB>
__device__ __forceinline__ void wgmma_ss_n192(float (&d)[96], uint32_t da, uint32_t db, int sc) {
  asm volatile("{\n.reg .pred p;\n.reg .b64 da, db;\n.reg .b32 hi;\nmov.b32 hi, 0x40000040;\nmov.b64 da, {%96, hi};\nmov.b64 db, {%97, hi};\nsetp.ne.b32 p, %98, 0;\n"
    "wgmma.mma_async.sync.aligned.m64n192k16.f32.bf16.bf16 "
    "{%0, %1, %2, %3, %4, %5, %6, %7, %8, %9, %10, %11, %12, %13, %14, %15, %16, %17, %18, %19, %20, %21, %22, %23, %24, %25, %26, %27, %28, %29, %30, %31, %32, %33, %34, %35, %36, %37, %38, %39, %40, %41, %42, %43, %44, %45, %46, %47, %48, %49, %50, %51, %52, %53, %54, %55, %56, %57, %58, %59, %60, %61, %62, %63, %64, %65, %66, %67, %68, %69, %70, %71, %72, %73, %74, %75, %76, %77, %78, %79, %80, %81, %82, %83, %84, %85, %86, %87, %88, %89, %90, %91, %92, %93, %94, %95}, "
    "da, db, p, 1, 1, %99, %100;\n}\n"
    : "+f"(d[0]), "+f"(d[1]), "+f"(d[2]), "+f"(d[3]), "+f"(d[4]), "+f"(d[5]), "+f"(d[6]), "+f"(d[7]), "+f"(d[8]), "+f"(d[9]), "+f"(d[10]), "+f"(d[11]), "+f"(d[12]), "+f"(d[13]), "+f"(d[14]), "+f"(d[15]), "+f"(d[16]), "+f"(d[17]), "+f"(d[18]), "+f"(d[19]), "+f"(d[20]), "+f"(d[21]), "+f"(d[22]), "+f"(d[23]), "+f"(d[24]), "+f"(d[25]), "+f"(d[26]), "+f"(d[27]), "+f"(d[28]), "+f"(d[29]), "+f"(d[30]), "+f"(d[31]), "+f"(d[32]), "+f"(d[33]), "+f"(d[34]), "+f"(d[35]), "+f"(d[36]), "+f"(d[37]), "+f"(d[38]), "+f"(d[39]), "+f"(d[40]), "+f"(d[41]), "+f"(d[42]), "+f"(d[43]), "+f"(d[44]), "+f"(d[45]), "+f"(d[46]), "+f"(d[47]), "+f"(d[48]), "+f"(d[49]), "+f"(d[50]), "+f"(d[51]), "+f"(d[52]), "+f"(d[53]), "+f"(d[54]), "+f"(d[55]), "+f"(d[56]), "+f"(d[57]), "+f"(d[58]), "+f"(d[59]), "+f"(d[60]), "+f"(d[61]), "+f"(d[62]), "+f"(d[63]), "+f"(d[64]), "+f"(d[65]), "+f"(d[66]), "+f"(d[67]), "+f"(d[68]), "+f"(d[69]), "+f"(d[70]), "+f"(d[71]), "+f"(d[72]), "+f"(d[73]), "+f"(d[74]), "+f"(d[75]), "+f"(d[76]), "+f"(d[77]), "+f"(d[78]), "+f"(d[79]), "+f"(d[80]), "+f"(d[81]), "+f"(d[82]), "+f"(d[83]), "+f"(d[84]), "+f"(d[85]), "+f"(d[86]), "+f"(d[87]), "+f"(d[88]), "+f"(d[89]), "+f"(d[90]), "+f"(d[91]), "+f"(d[92]), "+f"(d[93]), "+f"(d[94]), "+f"(d[95])
    : "r"(da), "r"(db), "r"(sc), "n"(TA), "n"(TB));
}
template <int TB>
__device__ __forceinline__ void wgmma_rs_n192(float (&d)[96], uint32_t a0, uint32_t a1, uint32_t a2, uint32_t a3, uint32_t db, int sc) {
  asm volatile("{\n.reg .pred p;\n.reg .b64 db;\n.reg .b32 hi;\nmov.b32 hi, 0x40000040;\nmov.b64 db, {%100, hi};\nsetp.ne.b32 p, %101, 0;\n"
    "wgmma.mma_async.sync.aligned.m64n192k16.f32.bf16.bf16 "
    "{%0, %1, %2, %3, %4, %5, %6, %7, %8, %9, %10, %11, %12, %13, %14, %15, %16, %17, %18, %19, %20, %21, %22, %23, %24, %25, %26, %27, %28, %29, %30, %31, %32, %33, %34, %35, %36, %37, %38, %39, %40, %41, %42, %43, %44, %45, %46, %47, %48, %49, %50, %51, %52, %53, %54, %55, %56, %57, %58, %59, %60, %61, %62, %63, %64, %65, %66, %67, %68, %69, %70, %71, %72, %73, %74, %75, %76, %77, %78, %79, %80, %81, %82, %83, %84, %85, %86, %87, %88, %89, %90, %91, %92, %93, %94, %95}, "
    "{%96, %97, %98, %99}, db, p, 1, 1, %102;\n}\n"
    : "+f"(d[0]), "+f"(d[1]), "+f"(d[2]), "+f"(d[3]), "+f"(d[4]), "+f"(d[5]), "+f"(d[6]), "+f"(d[7]), "+f"(d[8]), "+f"(d[9]), "+f"(d[10]), "+f"(d[11]), "+f"(d[12]), "+f"(d[13]), "+f"(d[14]), "+f"(d[15]), "+f"(d[16]), "+f"(d[17]), "+f"(d[18]), "+f"(d[19]), "+f"(d[20]), "+f"(d[21]), "+f"(d[22]), "+f"(d[23]), "+f"(d[24]), "+f"(d[25]), "+f"(d[26]), "+f"(d[27]), "+f"(d[28]), "+f"(d[29]), "+f"(d[30]), "+f"(d[31]), "+f"(d[32]), "+f"(d[33]), "+f"(d[34]), "+f"(d[35]), "+f"(d[36]), "+f"(d[37]), "+f"(d[38]), "+f"(d[39]), "+f"(d[40]), "+f"(d[41]), "+f"(d[42]), "+f"(d[43]), "+f"(d[44]), "+f"(d[45]), "+f"(d[46]), "+f"(d[47]), "+f"(d[48]), "+f"(d[49]), "+f"(d[50]), "+f"(d[51]), "+f"(d[52]), "+f"(d[53]), "+f"(d[54]), "+f"(d[55]), "+f"(d[56]), "+f"(d[57]), "+f"(d[58]), "+f"(d[59]), "+f"(d[60]), "+f"(d[61]), "+f"(d[62]), "+f"(d[63]), "+f"(d[64]), "+f"(d[65]), "+f"(d[66]), "+f"(d[67]), "+f"(d[68]), "+f"(d[69]), "+f"(d[70]), "+f"(d[71]), "+f"(d[72]), "+f"(d[73]), "+f"(d[74]), "+f"(d[75]), "+f"(d[76]), "+f"(d[77]), "+f"(d[78]), "+f"(d[79]), "+f"(d[80]), "+f"(d[81]), "+f"(d[82]), "+f"(d[83]), "+f"(d[84]), "+f"(d[85]), "+f"(d[86]), "+f"(d[87]), "+f"(d[88]), "+f"(d[89]), "+f"(d[90]), "+f"(d[91]), "+f"(d[92]), "+f"(d[93]), "+f"(d[94]), "+f"(d[95])
    : "r"(a0), "r"(a1), "r"(a2), "r"(a3), "r"(db), "r"(sc), "n"(TB));
}
template <int TB>
__device__ __forceinline__ void wgmma_rs_n64(float (&d)[32], uint32_t a0, uint32_t a1, uint32_t a2, uint32_t a3, uint32_t db, int sc) {
  asm volatile("{\n.reg .pred p;\n.reg .b64 db;\n.reg .b32 hi;\nmov.b32 hi, 0x40000040;\nmov.b64 db, {%36, hi};\nsetp.ne.b32 p, %37, 0;\n"
    "wgmma.mma_async.sync.aligned.m64n64k16.f32.bf16.bf16 "
    "{%0, %1, %2, %3, %4, %5, %6, %7, %8, %9, %10, %11, %12, %13, %14, %15, %16, %17, %18, %19, %20, %21, %22, %23, %24, %25, %26, %27, %28, %29, %30, %31}, "
    "{%32, %33, %34, %35}, db, p, 1, 1, %38;\n}\n"
    : "+f"(d[0]), "+f"(d[1]), "+f"(d[2]), "+f"(d[3]), "+f"(d[4]), "+f"(d[5]), "+f"(d[6]), "+f"(d[7]), "+f"(d[8]), "+f"(d[9]), "+f"(d[10]), "+f"(d[11]), "+f"(d[12]), "+f"(d[13]), "+f"(d[14]), "+f"(d[15]), "+f"(d[16]), "+f"(d[17]), "+f"(d[18]), "+f"(d[19]), "+f"(d[20]), "+f"(d[21]), "+f"(d[22]), "+f"(d[23]), "+f"(d[24]), "+f"(d[25]), "+f"(d[26]), "+f"(d[27]), "+f"(d[28]), "+f"(d[29]), "+f"(d[30]), "+f"(d[31])
    : "r"(a0), "r"(a1), "r"(a2), "r"(a3), "r"(db), "r"(sc), "n"(TB));
}
template <int TA, int TB>
__device__ __forceinline__ void wgmma_ss_n144(float (&d)[72], uint32_t da, uint32_t db, int sc) {
  asm volatile("{\n.reg .pred p;\n.reg .b64 da, db;\n.reg .b32 hi;\nmov.b32 hi, 0x40000040;\nmov.b64 da, {%72, hi};\nmov.b64 db, {%73, hi};\nsetp.ne.b32 p, %74, 0;\n"
    "wgmma.mma_async.sync.aligned.m64n144k16.f32.bf16.bf16 "
    "{%0, %1, %2, %3, %4, %5, %6, %7, %8, %9, %10, %11, %12, %13, %14, %15, %16, %17, %18, %19, %20, %21, %22, %23, %24, %25, %26, %27, %28, %29, %30, %31, %32, %33, %34, %35, %36, %37, %38, %39, %40, %41, %42, %43, %44, %45, %46, %47, %48, %49, %50, %51, %52, %53, %54, %55, %56, %57, %58, %59, %60, %61, %62, %63, %64, %65, %66, %67, %68, %69, %70, %71}, "
    "da, db, p, 1, 1, %75, %76;\n}\n"
    : "+f"(d[0]), "+f"(d[1]), "+f"(d[2]), "+f"(d[3]), "+f"(d[4]), "+f"(d[5]), "+f"(d[6]), "+f"(d[7]), "+f"(d[8]), "+f"(d[9]), "+f"(d[10]), "+f"(d[11]), "+f"(d[12]), "+f"(d[13]), "+f"(d[14]), "+f"(d[15]), "+f"(d[16]), "+f"(d[17]), "+f"(d[18]), "+f"(d[19]), "+f"(d[20]), "+f"(d[21]), "+f"(d[22]), "+f"(d[23]), "+f"(d[24]), "+f"(d[25]), "+f"(d[26]), "+f"(d[27]), "+f"(d[28]), "+f"(d[29]), "+f"(d[30]), "+f"(d[31]), "+f"(d[32]), "+f"(d[33]), "+f"(d[34]), "+f"(d[35]), "+f"(d[36]), "+f"(d[37]), "+f"(d[38]), "+f"(d[39]), "+f"(d[40]), "+f"(d[41]), "+f"(d[42]), "+f"(d[43]), "+f"(d[44]), "+f"(d[45]), "+f"(d[46]), "+f"(d[47]), "+f"(d[48]), "+f"(d[49]), "+f"(d[50]), "+f"(d[51]), "+f"(d[52]), "+f"(d[53]), "+f"(d[54]), "+f"(d[55]), "+f"(d[56]), "+f"(d[57]), "+f"(d[58]), "+f"(d[59]), "+f"(d[60]), "+f"(d[61]), "+f"(d[62]), "+f"(d[63]), "+f"(d[64]), "+f"(d[65]), "+f"(d[66]), "+f"(d[67]), "+f"(d[68]), "+f"(d[69]), "+f"(d[70]), "+f"(d[71])
    : "r"(da), "r"(db), "r"(sc), "n"(TA), "n"(TB));
}

__device__ __forceinline__ void fuse_weights(uint32_t sbase, uint8_t* sptr, int j, const __nv_bfloat16* __restrict__ wqkv_t,
                                             const __nv_bfloat16* __restrict__ wo_t, const __nv_bfloat16* __restrict__ wqkv_s,
                                             const __nv_bfloat16* __restrict__ wo_s) {
  const int m = j / 12, n0 = ((j % 12) >> 2) * 64, k0 = (j & 3) * 48;
  const __nv_bfloat16* wqkv = (m < 2) ? wqkv_t : wqkv_s;
  const __nv_bfloat16* wo = (m < 2) ? wo_t : wo_s;
  const int tid = threadIdx.x;
  const bool odd = m & 1;
  uint8_t* pA = sptr; uint8_t* pB = sptr + 24576;
  uint4 va[4], vb[3];
#pragma unroll
  for (int i = 0; i < 4; ++i) {
    const int u = tid + i * 384;
    const int row = odd ? (u >> 3) : (u / 24), cu = odd ? (u & 7) : (u % 24);
    va[i] = __ldg(reinterpret_cast<const uint4*>(odd ? (wo + row * 192 + n0 + cu * 8) : (wqkv + (n0 + row) * 576 + 192 + cu * 8)));
  }
#pragma unroll
  for (int i = 0; i < 3; ++i) {
    const int u = tid + i * 384, row = u / 24, cu = u % 24;
    vb[i] = __ldg(reinterpret_cast<const uint4*>(wqkv + (k0 + row) * 576 + (odd ? 384 : 0) + cu * 8));
  }
#pragma unroll
  for (int i = 0; i < 4; ++i) {
    const int u = tid + i * 384;
    const int row = odd ? (u >> 3) : (u / 24), cu = odd ? (u & 7) : (u % 24);
    *reinterpret_cast<uint4*>(pA + (cu >> 3) * 8192 + row * 128 + (((cu ^ row) & 7) << 4)) = va[i];
  }
#pragma unroll
  for (int i = 0; i < 3; ++i) {
    const int u = tid + i * 384, row = u / 24, cu = u % 24;
    *reinterpret_cast<uint4*>(pB + (cu >> 3) * 6144 + row * 128 + (((cu ^ row) & 7) << 4)) = vb[i];
  }
  fence_async_smem();
  __syncthreads();
  if (tid < 128) {
    float acc[24];
    const uint32_t dB = make_desc(sbase + 24576, 16, 1024);
    wg_fence();
    if (odd) {
      const uint32_t dA = make_desc(sbase, 8192, 1024);
#pragma unroll
      for (int kk = 0; kk < 12; ++kk) wgmma_ss_n48<1, 0>(acc, dA + kk * 128, dB + ((kk >> 2) * 384 + (kk & 3) * 2), kk > 0);
    } else {
      const uint32_t dA = make_desc(sbase, 16, 1024);
#pragma unroll
      for (int kk = 0; kk < 12; ++kk) wgmma_ss_n48<0, 0>(acc, dA + ((kk >> 2) * 512 + (kk & 3) * 2), dB + ((kk >> 2) * 384 + (kk & 3) * 2), kk > 0);
    }
    wg_commit();
    wg_wait<0>();
    fence_regs(acc);
    const int lane = tid & 31, r0 = n0 + (tid >> 5) * 16 + (lane >> 2);
    __nv_bfloat16* dst = g_w + (size_t)m * 3 * 192 * 64;
#pragma unroll
    for (int jj = 0; jj < 6; ++jj) {
      const int k = k0 + 8 * jj + 2 * (lane & 3);
      __nv_bfloat16* ch = dst + (k >> 6) * (192 * 64);
      *reinterpret_cast<uint32_t*>(ch + swz(r0, k & 63)) = pack_bf16(acc[4 * jj], acc[4 * jj + 1]);
      *reinterpret_cast<uint32_t*>(ch + swz(r0 + 8, k & 63)) = pack_bf16(acc[4 * jj + 2], acc[4 * jj + 3]);
    }
    __threadfence();
    named_bar(1, 128);
    if (tid == 0) atomicAdd(g_cnt + 16 + m, 1u);
  }
}

constexpr int W_BYTES = 3 * 192 * 128;
constexpr int WCH = 192 * 128;
constexpr int TILE_BYTES = 3 * 64 * 128;
constexpr int P1_SMEM = 2 * W_BYTES + 3 * TILE_BYTES + 128 + 1024;
constexpr int FS = 3472;

__device__ __forceinline__ void gemm_rs_w(float (&acc)[96], const uint32_t (&a)[48], uint32_t c0, uint32_t c1, uint32_t c2) {
  wg_fence();
#pragma unroll
  for (int kk = 0; kk < 12; ++kk) {
    const uint32_t base = (kk < 4) ? c0 : ((kk < 8) ? c1 : c2);
    wgmma_rs_n192<0>(acc, a[4 * kk], a[4 * kk + 1], a[4 * kk + 2], a[4 * kk + 3], make_desc(base + (kk & 3) * 32, 16, 1024), kk > 0);
  }
  wg_commit();
}
__global__ void __launch_bounds__(384, 1) p1_kernel(const __nv_bfloat16* __restrict__ x, const __nv_bfloat16* __restrict__ wqkv_t,
                                                    const __nv_bfloat16* __restrict__ wo_t, const __nv_bfloat16* __restrict__ wqkv_s,
                                                    const __nv_bfloat16* __restrict__ wo_s) {
  extern __shared__ uint8_t smem_raw[];
  const uint32_t sbase = (smem_u32(smem_raw) + 1023) & ~1023u;
  uint8_t* sptr = smem_raw + (sbase - smem_u32(smem_raw));
  if (blockIdx.x < 48) {
    PROF(0, 0, 0);
    pdl_launch();
    if (blockIdx.x == 0 && threadIdx.x >= 256 && threadIdx.x < 272) g_cnt[threadIdx.x - 256] = 0;
    fuse_weights(sbase, sptr, blockIdx.x, wqkv_t, wo_t, wqkv_s, wo_s);
    PROF(0, 0, 1);
    return;
  }
  const int bid = blockIdx.x - 48;
  const uint32_t sWA = sbase, sWB = sbase + W_BYTES, sH = sbase + 2 * W_BYTES;
  const uint32_t sX = sH + 2 * TILE_BYTES;
  const uint32_t bars = sH + 3 * TILE_BYTES;
  const int tid = threadIdx.x, warp = tid >> 5, lane = tid & 31;
  if (tid == 0) PROF(1, 3, 0);
  pdl_launch();
  if (tid == 0) {
    mbar_init(bars, 1); mbar_init(bars + 8, 1); mbar_init(bars + 16, 1); mbar_init(bars + 24, 8); mbar_init(bars + 32, 4); mbar_init(bars + 40, 4);
    mbar_init(bars + 48, 1); mbar_init(bars + 56, 1); mbar_init(bars + 64, 8); mbar_init(bars + 72, 1); mbar_init(bars + 80, 1);
    fence_mbar_init();
  }
  __syncthreads();

  if (warp >= 8) {
    asm volatile("setmaxnreg.dec.sync.aligned.u32 40;");
    if (warp == 8 && lane == 0) {
#pragma unroll 1
      for (int i = 0; i < 14; ++i) {
        const int wg = i / 7, tt = i - wg * 7;
        if (tt == 0) mbar_expect_tx(bars + 48 + 8 * wg, 7 * 3456);
        bulk_g2s(sWB + wg * TILE_BYTES + tt * FS, x + ((size_t)tt * N_ + (bid * 2 + wg) * 9) * C_, 3456, bars + 48 + 8 * wg);
      }
      wait_counter(g_cnt + 16, 12);
      fence_async_all();
      mbar_expect_tx(bars, WCH);
      bulk_g2s(sWA, g_w, WCH, bars);
      mbar_expect_tx(bars + 72, WCH);
      bulk_g2s(sWA + WCH, g_w + 192 * 64, WCH, bars + 72);
      mbar_expect_tx(bars + 80, WCH);
      bulk_g2s(sWA + 2 * WCH, g_w + 2 * 192 * 64, WCH, bars + 80);
      wait_counter(g_cnt + 17, 12);
      fence_async_all();
      mbar_wait(bars + 64, 0);
      mbar_expect_tx(bars + 8, W_BYTES);
      bulk_g2s(sWB, g_w + 3 * 192 * 64, W_BYTES, bars + 8);
      wait_counter(g_cnt + 18, 12);
      fence_async_all();
      mbar_wait(bars + 24, 0);
      mbar_expect_tx(bars + 16, W_BYTES);
      bulk_g2s(sWA, g_w + 2 * 3 * 192 * 64, W_BYTES, bars + 16);
    }
    __syncwarp();
#pragma unroll 1
    for (int wg = 0; wg < 2; ++wg) {
      named_bar(6 + 4 * wg, 256);
      const int ht = tid - 256, n0 = (bid * 2 + wg) * 9;
      const uint8_t* pX1 = sptr + 2 * W_BYTES + wg * TILE_BYTES;
      const uint8_t* pH2 = wg ? (sptr + W_BYTES + TILE_BYTES) : (sptr + 2 * W_BYTES + 2 * TILE_BYTES);
#pragma unroll 4
      for (int it = 0; it < 12; ++it) {
        const int idx = it * 128 + ht;
        if (idx < 1512) {
          const int i = idx / 72, off = idx - i * 72, tt = i / 3, ch = i - tt * 3;
          const int so = tt * FS + ch * 1152 + off * 16;
          const uint4 a = *reinterpret_cast<const uint4*>(pX1 + so), b = *reinterpret_cast<const uint4*>(pH2 + so);
          reinterpret_cast<uint4*>(g_h2 + ((size_t)i * N_ + n0) * 64)[off] = b;
          reinterpret_cast<uint4*>(g_x1 + ((size_t)tt * N_ + n0) * C_)[ch * 72 + off] = a;
        }
      }
    }
    return;
  }

  asm volatile("setmaxnreg.inc.sync.aligned.u32 232;");
  const int wg = warp >> 2, t = tid & 127, wl = warp & 3;
  const int n0 = (bid * 2 + wg) * 9;
  const uint32_t sHt = sH + wg * TILE_BYTES;
  PROF(1, wg, 0);
  uint8_t* pHt = sptr + 2 * W_BYTES + wg * TILE_BYTES;
  {
    const uint8_t* pX = sptr + W_BYTES + wg * TILE_BYTES;
    const int l8 = lane & 7;
    mbar_wait(bars + 48 + 8 * wg, 0);
    uint4 v[4][3];
#pragma unroll
    for (int it = 0; it < 4; ++it) {
      const int row = wl * 16 + it * 4 + (lane >> 3);
      const int j = row / 7, tt = row - j * 7;
#pragma unroll
      for (int c = 0; c < 3; ++c)
        v[it][c] = (row < 63) ? *reinterpret_cast<const uint4*>(pX + tt * FS + j * 384 + (l8 + 8 * c) * 16) : make_uint4(0, 0, 0, 0);
    }
    __syncwarp();
    if (lane == 0) mbar_arrive(bars + 64);
#pragma unroll
    for (int it = 0; it < 4; ++it) {
      const int row = wl * 16 + it * 4 + (lane >> 3);
      float f[24];
#pragma unroll
      for (int c = 0; c < 3; ++c) {
        f[8 * c] = bf_lo(v[it][c].x); f[8 * c + 1] = bf_hi(v[it][c].x); f[8 * c + 2] = bf_lo(v[it][c].y); f[8 * c + 3] = bf_hi(v[it][c].y);
        f[8 * c + 4] = bf_lo(v[it][c].z); f[8 * c + 5] = bf_hi(v[it][c].z); f[8 * c + 6] = bf_lo(v[it][c].w); f[8 * c + 7] = bf_hi(v[it][c].w);
      }
      float s = 0.f;
#pragma unroll
      for (int e = 0; e < 24; ++e) s += f[e];
      s += __shfl_xor_sync(0xffffffffu, s, 1); s += __shfl_xor_sync(0xffffffffu, s, 2); s += __shfl_xor_sync(0xffffffffu, s, 4);
      const float mean = s * (1.f / 192.f);
      float ss = 0.f;
#pragma unroll
      for (int e = 0; e < 24; ++e) { f[e] -= mean; ss += f[e] * f[e]; }
      ss += __shfl_xor_sync(0xffffffffu, ss, 1); ss += __shfl_xor_sync(0xffffffffu, ss, 2); ss += __shfl_xor_sync(0xffffffffu, ss, 4);
      const float rstd = 1.f / sqrtf(ss * (1.f / 192.f) + 1e-5f);
#pragma unroll
      for (int c = 0; c < 3; ++c)
        *reinterpret_cast<uint4*>(pHt + c * 8192 + row * 128 + (((l8 ^ row) & 7) << 4)) =
            make_uint4(pack_bf16(f[8 * c] * rstd, f[8 * c + 1] * rstd), pack_bf16(f[8 * c + 2] * rstd, f[8 * c + 3] * rstd),
                       pack_bf16(f[8 * c + 4] * rstd, f[8 * c + 5] * rstd), pack_bf16(f[8 * c + 6] * rstd, f[8 * c + 7] * rstd));
    }
  }
  PROF(1, wg, 1);
  fence_async_smem();
  named_bar(1 + wg, 128);

  const int g = lane >> 2, q = lane & 3;
  const int r0 = wl * 16 + g, r1 = r0 + 8;
  float acc[96];
  uint32_t af[48];
  mbar_wait(bars, 0);
  if (wg == 1) named_bar(7, 256);
  PROF(1, wg, 2);
  wg_fence();
#pragma unroll
  for (int kk = 0; kk < 12; ++kk) {
    if (kk == 4) mbar_wait(bars + 72, 0);
    if (kk == 8) mbar_wait(bars + 80, 0);
    wgmma_ss_n192<0, 0>(acc, make_desc(sHt + (kk >> 2) * 8192 + (kk & 3) * 32, 16, 1024), make_desc(sWA + (kk >> 2) * WCH + (kk & 3) * 32, 16, 1024), kk > 0);
  }
  wg_commit();
  wg_wait<0>();
  fence_regs(acc);
  PROF(1, wg, 3);
  if (wg == 0) named_arrive(7, 256);
  if (lane == 0) mbar_arrive(bars + 24);
#pragma unroll
  for (int i = 0; i < 48; ++i) af[i] = pack_bf16(acc[2 * i], acc[2 * i + 1]);
  float sc[32];
  wg_fence();
#pragma unroll
  for (int kk = 0; kk < 12; ++kk)
    wgmma_rs_n64<0>(sc, af[4 * kk], af[4 * kk + 1], af[4 * kk + 2], af[4 * kk + 3],
                    make_desc(sHt + (kk >> 2) * 8192 + (kk & 3) * 32, 16, 1024), kk > 0);
  wg_commit();
  wg_wait<0>();
  fence_regs(sc);
  PROF(1, wg, 4);
  uint32_t pf[16];
  {
    const int g0 = r0 / 7, g1 = r1 / 7;
    float mx0 = -INFINITY, mx1 = -INFINITY;
#pragma unroll
    for (int j = 0; j < 8; ++j) {
#pragma unroll
      for (int e = 0; e < 2; ++e) {
        const int col = 8 * j + 2 * q + e;
        const int cg = col / 7;
        if (cg != g0) sc[4 * j + e] = -INFINITY;
        if (cg != g1) sc[4 * j + 2 + e] = -INFINITY;
        mx0 = fmaxf(mx0, sc[4 * j + e]);
        mx1 = fmaxf(mx1, sc[4 * j + 2 + e]);
      }
    }
    mx0 = fmaxf(mx0, __shfl_xor_sync(0xffffffffu, mx0, 1)); mx0 = fmaxf(mx0, __shfl_xor_sync(0xffffffffu, mx0, 2));
    mx1 = fmaxf(mx1, __shfl_xor_sync(0xffffffffu, mx1, 1)); mx1 = fmaxf(mx1, __shfl_xor_sync(0xffffffffu, mx1, 2));
    float l0 = 0.f, l1 = 0.f;
#pragma unroll
    for (int j = 0; j < 8; ++j) {
#pragma unroll
      for (int e = 0; e < 2; ++e) {
        sc[4 * j + e] = ex2((sc[4 * j + e] - mx0) * SM_SCALE_LOG2);
        sc[4 * j + 2 + e] = ex2((sc[4 * j + 2 + e] - mx1) * SM_SCALE_LOG2);
        l0 += sc[4 * j + e];
        l1 += sc[4 * j + 2 + e];
      }
    }
    l0 += __shfl_xor_sync(0xffffffffu, l0, 1); l0 += __shfl_xor_sync(0xffffffffu, l0, 2);
    l1 += __shfl_xor_sync(0xffffffffu, l1, 1); l1 += __shfl_xor_sync(0xffffffffu, l1, 2);
    const float i0 = 1.f / l0, i1 = 1.f / l1;
#pragma unroll
    for (int j = 0; j < 8; ++j) {
      pf[2 * j] = pack_bf16(sc[4 * j] * i0, sc[4 * j + 1] * i0);
      pf[2 * j + 1] = pack_bf16(sc[4 * j + 2] * i1, sc[4 * j + 3] * i1);
    }
  }
  wg_fence();
#pragma unroll
  for (int kk = 0; kk < 4; ++kk)
    wgmma_rs_n192<1>(acc, pf[4 * kk], pf[4 * kk + 1], pf[4 * kk + 2], pf[4 * kk + 3], make_desc(sHt + kk * 2048, 8192, 1024), kk > 0);
  wg_commit();
  wg_wait<0>();
  fence_regs(acc);
#pragma unroll
  for (int i = 0; i < 48; ++i) af[i] = pack_bf16(acc[2 * i], acc[2 * i + 1]);
  PROF(1, wg, 5);
  named_bar(1 + wg, 128);
  if (lane == 0) {
    mbar_expect_tx(bars + 32 + 8 * wg, (wl == 3 ? 1 : 2) * 3456);
#pragma unroll 1
    for (int tt = wl; tt < 7; tt += 4) bulk_g2s(sHt + tt * FS, x + ((size_t)tt * N_ + n0) * C_, 3456, bars + 32 + 8 * wg);
  }
  mbar_wait(bars + 8, 0);
  PROF(1, wg, 6);
  gemm_rs_w(acc, af, sWB, sWB + WCH, sWB + 2 * WCH);
  uint32_t xr[48];
  {
    const int j0 = r0 / 7, t0 = r0 - j0 * 7, j1 = min(r1, 62) / 7, t1 = min(r1, 62) - j1 * 7;
    const uint8_t* p0 = pHt + t0 * FS + j0 * 384 + q * 4;
    const uint8_t* p1 = pHt + t1 * FS + j1 * 384 + q * 4;
    mbar_wait(bars + 32 + 8 * wg, 0);
#pragma unroll
    for (int j = 0; j < 24; ++j) { xr[2 * j] = *reinterpret_cast<const uint32_t*>(p0 + 16 * j); xr[2 * j + 1] = *reinterpret_cast<const uint32_t*>(p1 + 16 * j); }
  }
  wg_wait<0>();
  fence_regs(acc);
  PROF(1, wg, 7);
  named_arrive(8 + wg, 256);
  {
    float s0 = 0.f, s1 = 0.f;
#pragma unroll
    for (int j = 0; j < 24; ++j) {
      const uint32_t a = pack_bf16(bf_lo(xr[2 * j]) + acc[4 * j], bf_hi(xr[2 * j]) + acc[4 * j + 1]);
      const uint32_t b = pack_bf16(bf_lo(xr[2 * j + 1]) + acc[4 * j + 2], bf_hi(xr[2 * j + 1]) + acc[4 * j + 3]);
      xr[2 * j] = a; xr[2 * j + 1] = b;
      acc[4 * j] = bf_lo(a); acc[4 * j + 1] = bf_hi(a); acc[4 * j + 2] = bf_lo(b); acc[4 * j + 3] = bf_hi(b);
      s0 += acc[4 * j] + acc[4 * j + 1];
      s1 += acc[4 * j + 2] + acc[4 * j + 3];
    }
    s0 += __shfl_xor_sync(0xffffffffu, s0, 1); s0 += __shfl_xor_sync(0xffffffffu, s0, 2);
    s1 += __shfl_xor_sync(0xffffffffu, s1, 1); s1 += __shfl_xor_sync(0xffffffffu, s1, 2);
    const float mean0 = s0 * (1.f / 192.f), mean1 = s1 * (1.f / 192.f);
    float q0 = 0.f, q1 = 0.f;
#pragma unroll
    for (int j = 0; j < 24; ++j) {
      acc[4 * j] -= mean0; acc[4 * j + 1] -= mean0; acc[4 * j + 2] -= mean1; acc[4 * j + 3] -= mean1;
      q0 += acc[4 * j] * acc[4 * j] + acc[4 * j + 1] * acc[4 * j + 1];
      q1 += acc[4 * j + 2] * acc[4 * j + 2] + acc[4 * j + 3] * acc[4 * j + 3];
    }
    q0 += __shfl_xor_sync(0xffffffffu, q0, 1); q0 += __shfl_xor_sync(0xffffffffu, q0, 2);
    q1 += __shfl_xor_sync(0xffffffffu, q1, 1); q1 += __shfl_xor_sync(0xffffffffu, q1, 2);
    const float rs0 = 1.f / sqrtf(q0 * (1.f / 192.f) + 1e-5f), rs1 = 1.f / sqrtf(q1 * (1.f / 192.f) + 1e-5f);
#pragma unroll
    for (int j = 0; j < 24; ++j) {
      af[2 * j] = pack_bf16(acc[4 * j] * rs0, acc[4 * j + 1] * rs0);
      af[2 * j + 1] = pack_bf16(acc[4 * j + 2] * rs1, acc[4 * j + 3] * rs1);
    }
  }
  PROF(1, wg, 8);
  const int lrow = wl * 16 + ((lane >> 3) & 1) * 8 + (lane & 7), uh = lane >> 4;
  const int lj = lrow / 7, lt = lrow - lj * 7;
  const bool lvalid = lrow < 63;
  const uint32_t offX = lvalid ? (uint32_t)(lt * FS + lj * 384 + uh * 16) : 3456u;
  const uint32_t offH = lvalid ? (uint32_t)(lt * FS + lj * 128) : 3456u;
  const int lph = (n0 + lj) & 7;
  const uint32_t sStH = wg ? (sWB + TILE_BYTES) : sX;
  PROF(1, wg, 12);
  if (wg == 1) named_bar(8, 256);
  named_bar(1 + wg, 128);
  PROF(1, wg, 13);
#pragma unroll
  for (int i = 0; i < 12; ++i) {
    stsm_x4(sHt + offX + (lvalid ? i * 32 : 0), xr[4 * i], xr[4 * i + 1], xr[4 * i + 2], xr[4 * i + 3]);
    const int u = 2 * i + uh;
    stsm_x4(sStH + offH + (lvalid ? (uint32_t)((u >> 3) * 1152 + (((u ^ lph) & 7) << 4)) : 0u), af[4 * i], af[4 * i + 1], af[4 * i + 2], af[4 * i + 3]);
  }
  PROF(1, wg, 14);
  named_arrive(6 + 4 * wg, 256);
  mbar_wait(bars + 16, 0);
  PROF(1, wg, 9);
  gemm_rs_w(acc, af, sWA, sWA + WCH, sWA + 2 * WCH);
  PROF(1, wg, 16);
  wg_wait<0>();
  fence_regs(acc);
  PROF(1, wg, 10);
#pragma unroll
  for (int i = 0; i < 48; ++i) af[i] = pack_bf16(acc[2 * i], acc[2 * i + 1]);
  if (wg == 0) named_bar(9, 256);
  const uint32_t sStQ = sWB + (wg ? 0 : 2 * TILE_BYTES);
#pragma unroll
  for (int i = 0; i < 12; ++i) {
    const int u = 2 * i + uh;
    stsm_x4(sStQ + offH + (lvalid ? (uint32_t)((u >> 3) * 1152 + (((u ^ lph) & 7) << 4)) : 0u), af[4 * i], af[4 * i + 1], af[4 * i + 2], af[4 * i + 3]);
  }
  named_bar(1 + wg, 128);
#pragma unroll 4
  for (int it = 0; it < 12; ++it) {
    const int idx = it * 128 + t;
    if (idx < 1512) {
      const int i = idx / 72, off = idx - i * 72, tt = i / 3, ch = i - tt * 3;
      reinterpret_cast<uint4*>(g_q2 + ((size_t)i * N_ + n0) * 64)[off] = *reinterpret_cast<const uint4*>(sptr + (sStQ - sbase) + tt * FS + ch * 1152 + off * 16);
    }
  }
  PROF(1, wg, 11);
}

constexpr int KB = 144;
constexpr int KCH = KB * 128;
constexpr int STAGE_BYTES = 3 * KCH;
constexpr int NSTAGE = 3;
constexpr int P2_Q_OFF = NSTAGE * STAGE_BYTES;
constexpr int P2_ML_OFF = P2_Q_OFF + 2 * TILE_BYTES;
constexpr int P2_BAR_OFF = P2_ML_OFF + 2048;
constexpr int P2_SMEM = P2_BAR_OFF + 128 + 1024;

constexpr int OPITCH = 400;
__device__ __forceinline__ uint32_t add_bf2(uint32_t a, uint32_t b) { return pack_bf16(bf_lo(a) + bf_lo(b), bf_hi(a) + bf_hi(b)); }

__global__ void __cluster_dims__(2, 1, 1) __launch_bounds__(384, 1) p2_kernel(__nv_bfloat16* __restrict__ out) {
  extern __shared__ uint8_t smem_raw[];
  const uint32_t sbase = (smem_u32(smem_raw) + 1023) & ~1023u;
  uint8_t* sptr = smem_raw + (sbase - smem_u32(smem_raw));
  const uint32_t sQ = sbase + P2_Q_OFF, sML = sbase + P2_ML_OFF, bars = sbase + P2_BAR_OFF;
  const uint32_t bFull = bars, bEmpty = bars + 24, bQ0 = bars + 48, bQ1 = bars + 64, bW = bars + 80, bXFree = bars + 88, bXFull = bars + 96, bQ0Free = bars + 104;
  const int tid = threadIdx.x, lane = tid & 31;
  const int warp = __shfl_sync(0xffffffffu, tid >> 5, 0);
  const int cl = blockIdx.x >> 1, rank = blockIdx.x & 1;
  if (tid == 0) PROF(2, 3, 0);
  if (tid == 0) {
    for (int i = 0; i < NSTAGE; ++i) { mbar_init(bFull + 8 * i, 1); mbar_init(bEmpty + 8 * i, 8); }
    for (int i = 0; i < 2; ++i) { mbar_init(bQ0 + 8 * i, 1); mbar_init(bQ1 + 8 * i, 1); }
    mbar_init(bQ0Free, rank ? 8 : 4);
    mbar_init(bW, 1); mbar_init(bXFree, 8); mbar_init(bXFull, 1);
    mbar_expect_tx(bXFull, 13 * 128 * 16);
    fence_mbar_init();
  }
  const int f = cl / 9, c = cl - f * 9;
  const int nmain = 5 - rank;
  const int ntot = nmain + 1;
  const uint32_t sW0 = sbase + (ntot % NSTAGE) * STAGE_BYTES, sW1 = sW0 + WCH, sW2 = sbase + ((ntot + 1) % NSTAGE) * STAGE_BYTES;
  cluster_sync_all();
  pdl_wait();
  if (blockIdx.x == 0 && tid < 4) g_cnt[16 + tid] = 0;

  if (warp >= 8) {
    asm volatile("setmaxnreg.dec.sync.aligned.u32 40;");
    if (warp == 8 && lane == 0) {
      const __nv_bfloat16* kv = g_h2 + (size_t)(f * 3) * (N_ * 64);
#pragma unroll 1
      for (int i = 0; i < ntot; ++i) {
        const int blk = (i == 0) ? c : (rank * 5 + i - 1);
        const int st = i % NSTAGE;
        if (i >= NSTAGE) mbar_wait(bEmpty + 8 * st, ((i / NSTAGE) - 1) & 1);
        if (i == 2) mbar_wait(bQ0Free, 0);
        mbar_expect_tx(bFull + 8 * st, STAGE_BYTES);
#pragma unroll
        for (int ch = 0; ch < 3; ++ch) bulk_g2s(sbase + st * STAGE_BYTES + ch * KCH, kv + (size_t)ch * (N_ * 64) + (size_t)blk * KB * 64, KCH, bFull + 8 * st);
      }
      const __nv_bfloat16* wsrc = g_w + 3 * 3 * 192 * 64;
      mbar_expect_tx(bW, W_BYTES);
      mbar_wait(bEmpty + 8 * (ntot % NSTAGE), ((ntot / NSTAGE) - 1) & 1);
      bulk_g2s(sW0, wsrc, 2 * WCH, bW);
      mbar_wait(bEmpty + 8 * ((ntot + 1) % NSTAGE), (((ntot + 1) / NSTAGE) - 1) & 1);
      bulk_g2s(sW2, wsrc + 2 * 192 * 64, WCH, bW);
    } else if (warp == 9 && lane == 0) {
      const __nv_bfloat16* qsrc = g_q2 + (size_t)(f * 3) * (N_ * 64);
#pragma unroll 1
      for (int i = 0; i < 4; ++i) {
        const int sg = i >> 1, w = i & 1;
        if (sg == 0 && rank == 0 && w == 1) continue;
        if (i == 2) mbar_wait(bFull, 0);
        const int qr = sg ? (128 * c + 64 * w) : (rank ? 1152 + 64 * w : 1280);
        const uint32_t bar = (sg ? bQ1 : bQ0) + 8 * w, dst = (sg ? sQ : sbase + 2 * STAGE_BYTES) + w * TILE_BYTES;
        mbar_expect_tx(bar, TILE_BYTES);
#pragma unroll
        for (int ch = 0; ch < 3; ++ch) bulk_g2s(dst + ch * 8192, qsrc + (size_t)ch * (N_ * 64) + (size_t)qr * 64, 8192, bar);
      }
    }
    if (warp >= 10 && (rank || warp == 10)) {
      named_bar(6 + warp - 10, 160);
      if (lane == 0) { __threadfence(); atomicAdd(g_cnt + f, 1u); }
    }
    return;
  }

  asm volatile("setmaxnreg.inc.sync.aligned.u32 232;");
  const int w = warp >> 2, wl = warp & 3, t = tid & 127;
  const int g = lane >> 2, q = lane & 3;
  const int r0 = wl * 16 + g;
  const uint32_t sQt = sQ + w * TILE_BYTES;
  PROF(2, w, 0);
  float o[96];
  float m0, m1, l0, l1;
  {
    const int nrel = w ? ntot : (ntot + rank);
    int phase = 0;
    if (w == 1) named_arrive(4, 256);
    auto acquire = [&]() { named_bar(4 + w, 256); };
    auto release = [&]() { ++phase; if (phase <= nrel) named_arrive(4 + (w ^ 1), 256); };
    const bool skip0 = (rank == 0 && w == 1);
    int k = 0;
    uint32_t pf[36];
    uint32_t sK, bE;
    float sc[72];
    auto next_stage = [&]() {
      const int st = k % NSTAGE;
      sK = sbase + st * STAGE_BYTES; bE = bEmpty + 8 * st;
      mbar_wait(bFull + 8 * st, (k / NSTAGE) & 1);
      PROF(2, w, 2 + 3 * k);
    };
    auto issue_s = [&](uint32_t dQ) {
      const uint32_t dK = make_desc(sK, 16, 1024);
#pragma unroll
      for (int kk = 0; kk < 12; ++kk)
        wgmma_ss_n144<0, 0>(sc, dQ + ((kk >> 2) * 512 + (kk & 3) * 2), dK + ((kk >> 2) * (KCH / 16) + (kk & 3) * 2), kk > 0);
      wg_commit();
    };
    auto issue_pv = [&](uint32_t sV, int acc) {
      const uint32_t dV = make_desc(sV, KCH, 1024);
#pragma unroll
      for (int kk = 0; kk < 9; ++kk)
        wgmma_rs_n192<1>(o, pf[4 * kk], pf[4 * kk + 1], pf[4 * kk + 2], pf[4 * kk + 3], dV + kk * 128, acc || (kk > 0));
      wg_commit();
    };
    float a0, a1;
    auto softmax = [&]() {
      float mx0 = sc[0], mx1 = sc[2];
#pragma unroll
      for (int j = 0; j < 18; ++j) {
        mx0 = fmaxf(mx0, fmaxf(sc[4 * j], sc[4 * j + 1]));
        mx1 = fmaxf(mx1, fmaxf(sc[4 * j + 2], sc[4 * j + 3]));
      }
      mx0 = fmaxf(mx0, __shfl_xor_sync(0xffffffffu, mx0, 1)); mx0 = fmaxf(mx0, __shfl_xor_sync(0xffffffffu, mx0, 2));
      mx1 = fmaxf(mx1, __shfl_xor_sync(0xffffffffu, mx1, 1)); mx1 = fmaxf(mx1, __shfl_xor_sync(0xffffffffu, mx1, 2));
      const float mn0 = fmaxf(m0, mx0), mn1 = fmaxf(m1, mx1);
      a0 = ex2((m0 - mn0) * SM_SCALE_LOG2); a1 = ex2((m1 - mn1) * SM_SCALE_LOG2);
      m0 = mn0; m1 = mn1;
      const float ms0 = mn0 * SM_SCALE_LOG2, ms1 = mn1 * SM_SCALE_LOG2;
      float ls0 = 0.f, ls1 = 0.f;
#pragma unroll
      for (int j = 0; j < 18; ++j) {
        sc[4 * j] = ex2(fmaf(sc[4 * j], SM_SCALE_LOG2, -ms0)); sc[4 * j + 1] = ex2(fmaf(sc[4 * j + 1], SM_SCALE_LOG2, -ms0));
        sc[4 * j + 2] = ex2(fmaf(sc[4 * j + 2], SM_SCALE_LOG2, -ms1)); sc[4 * j + 3] = ex2(fmaf(sc[4 * j + 3], SM_SCALE_LOG2, -ms1));
        ls0 += sc[4 * j] + sc[4 * j + 1]; ls1 += sc[4 * j + 2] + sc[4 * j + 3];
      }
      l0 = l0 * a0 + ls0; l1 = l1 * a1 + ls1;
    };
    const uint32_t dQ1 = make_desc(sQt, 16, 1024);
    m0 = m1 = -INFINITY; l0 = l1 = 0.f;
    if (skip0) {
      if (lane == 0) mbar_arrive(bEmpty);
      k = 1;
    }
    mbar_wait((skip0 ? bQ1 : bQ0) + 8 * w, 0);
    PROF(2, w, 1);
    next_stage();
    acquire();
    wg_fence();
    issue_s(skip0 ? dQ1 : make_desc(sbase + 2 * STAGE_BYTES + w * TILE_BYTES, 16, 1024));
    release();
    wg_wait<0>();
    fence_regs(sc);
    PROF(2, w, 3 + 3 * k);
    if (!skip0 && lane == 0) mbar_arrive(bQ0Free);
    softmax();
#pragma unroll
    for (int j = 0; j < 36; ++j) pf[j] = pack_bf16(sc[2 * j], sc[2 * j + 1]);
    ++k;
    mbar_wait(bQ1 + 8 * w, 0);
#pragma unroll 1
    for (; k < ntot; ++k) {
      const uint32_t sV = sK, bEv = bE;
      next_stage();
      acquire();
      wg_fence();
      issue_s(dQ1);
      issue_pv(sV, k > 2);
      release();
      float4 ml0;
      if (k == 1) {
        ml0 = make_float4(m0, m1, l0, l1);
        m0 = m1 = -INFINITY; l0 = l1 = 0.f;
      }
      wg_wait<1>();
      fence_regs(sc);
      PROF(2, w, 3 + 3 * k);
      if (k == ntot - 1 && lane == 0) mbar_arrive_remote(mapa(bXFree, rank ^ 1));
      softmax();
      wg_wait<0>();
      fence_regs(o);
      if (lane == 0) mbar_arrive(bEv);
      if (k == 1) {
        ml0.z += __shfl_xor_sync(0xffffffffu, ml0.z, 1); ml0.z += __shfl_xor_sync(0xffffffffu, ml0.z, 2);
        ml0.w += __shfl_xor_sync(0xffffffffu, ml0.w, 1); ml0.w += __shfl_xor_sync(0xffffffffu, ml0.w, 2);
        const int slot = cl * 3 + (rank ? w : 2);
        if (rank || wl == 0) {
          uint4* po = g_part + (size_t)slot * (12 * 128) + t;
#pragma unroll
          for (int j = 0; j < 12; ++j)
            po[j * 128] = make_uint4(pack_bf16(o[8 * j], o[8 * j + 1]), pack_bf16(o[8 * j + 2], o[8 * j + 3]), pack_bf16(o[8 * j + 4], o[8 * j + 5]), pack_bf16(o[8 * j + 6], o[8 * j + 7]));
          g_pml[slot * 128 + t] = ml0;
        }
        named_arrive(6 + w, 160);
      } else {
#pragma unroll
        for (int j = 0; j < 24; ++j) { o[4 * j] *= a0; o[4 * j + 1] *= a0; o[4 * j + 2] *= a1; o[4 * j + 3] *= a1; }
      }
#pragma unroll
      for (int j = 0; j < 36; ++j) pf[j] = pack_bf16(sc[2 * j], sc[2 * j + 1]);
    }
    acquire();
    wg_fence();
    issue_pv(sK, 1);
    release();
    wg_wait<0>();
    fence_regs(o);
    if (lane == 0) mbar_arrive(bE);
    PROF(2, w, 1 + 3 * k);
    l0 += __shfl_xor_sync(0xffffffffu, l0, 1); l0 += __shfl_xor_sync(0xffffffffu, l0, 2);
    l1 += __shfl_xor_sync(0xffffffffu, l1, 1); l1 += __shfl_xor_sync(0xffffffffu, l1, 2);
    PROF(2, w, 20);
    if (w != rank) {
      mbar_wait_cluster(bXFree, 0);
      const uint32_t rq = mapa(sQ, rank ^ 1) + t * 16, rb = mapa(bXFull, rank ^ 1);
#pragma unroll
      for (int i = 0; i < 12; ++i)
        st_async_v4(rq + i * 2048, __uint_as_float(pack_bf16(o[8 * i], o[8 * i + 1])), __uint_as_float(pack_bf16(o[8 * i + 2], o[8 * i + 3])),
                    __uint_as_float(pack_bf16(o[8 * i + 4], o[8 * i + 5])), __uint_as_float(pack_bf16(o[8 * i + 6], o[8 * i + 7])), rb);
      st_async_v4(mapa(sML, rank ^ 1) + t * 16, m0, m1, l0, l1, rb);
      PROF(2, w, 21);
      if (rank == 0) return;
    }
  }

  const bool recv = (w == rank);
  mbar_wait(bW, 0);
  const uint32_t sT = sW2 + WCH;
  const int grow = f * N_ + (recv ? (128 * c + 64 * w) : (1152 + 16 * c));
  uint32_t af[48];
  if (recv) {
    mbar_wait_cluster(bXFull, 0);
    PROF(2, w, 17);
    const float4 ml = *reinterpret_cast<const float4*>(sptr + P2_ML_OFF + t * 16);
    const float mn0 = fmaxf(m0, ml.x), mn1 = fmaxf(m1, ml.y);
    float a0 = ex2((m0 - mn0) * SM_SCALE_LOG2), a1 = ex2((m1 - mn1) * SM_SCALE_LOG2);
    float b0 = ex2((ml.x - mn0) * SM_SCALE_LOG2), b1 = ex2((ml.y - mn1) * SM_SCALE_LOG2);
    const float i0 = 1.f / (a0 * l0 + b0 * ml.z), i1 = 1.f / (a1 * l1 + b1 * ml.w);
    a0 *= i0; b0 *= i0; a1 *= i1; b1 *= i1;
#pragma unroll
    for (int i = 0; i < 12; ++i) {
      const uint4 v = *reinterpret_cast<const uint4*>(sptr + P2_Q_OFF + i * 2048 + t * 16);
      af[4 * i] = pack_bf16(a0 * o[8 * i] + b0 * bf_lo(v.x), a0 * o[8 * i + 1] + b0 * bf_hi(v.x));
      af[4 * i + 1] = pack_bf16(a1 * o[8 * i + 2] + b1 * bf_lo(v.y), a1 * o[8 * i + 3] + b1 * bf_hi(v.y));
      af[4 * i + 2] = pack_bf16(a0 * o[8 * i + 4] + b0 * bf_lo(v.z), a0 * o[8 * i + 5] + b0 * bf_hi(v.z));
      af[4 * i + 3] = pack_bf16(a1 * o[8 * i + 6] + b1 * bf_lo(v.w), a1 * o[8 * i + 7] + b1 * bf_hi(v.w));
    }
  } else {
    if (t == 0) wait_counter(g_cnt + f, 27);
    named_bar(1 + w, 128);
    const int slot0 = f * 27 + (c >> 2), tl = (c & 3) * 32 + lane;
    float4 mlv[9]; uint4 v[9][3];
#pragma unroll
    for (int i = 0; i < 9; ++i) {
      mlv[i] = __ldcg(g_pml + (slot0 + 3 * i) * 128 + tl);
#pragma unroll
      for (int j = 0; j < 3; ++j) v[i][j] = __ldcg(g_part + (size_t)(slot0 + 3 * i) * (12 * 128) + (wl * 3 + j) * 128 + tl);
    }
    float mn0 = mlv[0].x, mn1 = mlv[0].y;
#pragma unroll
    for (int i = 1; i < 9; ++i) { mn0 = fmaxf(mn0, mlv[i].x); mn1 = fmaxf(mn1, mlv[i].y); }
    float s0 = 0.f, s1 = 0.f;
#pragma unroll
    for (int i = 0; i < 9; ++i) {
      mlv[i].x = ex2((mlv[i].x - mn0) * SM_SCALE_LOG2); mlv[i].y = ex2((mlv[i].y - mn1) * SM_SCALE_LOG2);
      s0 += mlv[i].x * mlv[i].z; s1 += mlv[i].y * mlv[i].w;
    }
    s0 = 1.f / s0; s1 = 1.f / s1;
    uint8_t* pT = sptr + (sT - sbase);
#pragma unroll
    for (int j = 0; j < 3; ++j) {
      float x[8] = {};
#pragma unroll
      for (int i = 0; i < 9; ++i) {
        x[0] += mlv[i].x * bf_lo(v[i][j].x); x[1] += mlv[i].x * bf_hi(v[i][j].x); x[2] += mlv[i].y * bf_lo(v[i][j].y); x[3] += mlv[i].y * bf_hi(v[i][j].y);
        x[4] += mlv[i].x * bf_lo(v[i][j].z); x[5] += mlv[i].x * bf_hi(v[i][j].z); x[6] += mlv[i].y * bf_lo(v[i][j].w); x[7] += mlv[i].y * bf_hi(v[i][j].w);
      }
      const int col = (wl * 3 + j) * 16 + 2 * q;
      *reinterpret_cast<uint32_t*>(pT + g * OPITCH + col * 2) = pack_bf16(x[0] * s0, x[1] * s0);
      *reinterpret_cast<uint32_t*>(pT + (g + 8) * OPITCH + col * 2) = pack_bf16(x[2] * s1, x[3] * s1);
      *reinterpret_cast<uint32_t*>(pT + g * OPITCH + col * 2 + 16) = pack_bf16(x[4] * s0, x[5] * s0);
      *reinterpret_cast<uint32_t*>(pT + (g + 8) * OPITCH + col * 2 + 16) = pack_bf16(x[6] * s1, x[7] * s1);
    }
    named_bar(1 + w, 128);
#pragma unroll
    for (int j = 0; j < 24; ++j) {
      af[2 * j] = *reinterpret_cast<const uint32_t*>(pT + g * OPITCH + j * 16 + q * 4);
      af[2 * j + 1] = *reinterpret_cast<const uint32_t*>(pT + (g + 8) * OPITCH + j * 16 + q * 4);
    }
  }
  PROF(2, w, 18);
  gemm_rs_w(o, af, sW0, sW1, sW2);
  const int nit = recv ? 12 : 3;
  uint4 xv[12];
  {
    const uint4* src = reinterpret_cast<const uint4*>(g_x1 + (size_t)grow * C_) + t;
#pragma unroll
    for (int it = 0; it < 12; ++it) if (it < nit) xv[it] = __ldcg(src + it * 128);
  }
  named_bar(1 + w, 128);
  wg_wait<0>();
  fence_regs(o);
  PROF(2, w, 22);
  const uint32_t sS = recv ? sQ : sT;
  if (recv || wl == 0) {
    const uint32_t addr = sS + (wl * 16 + ((lane >> 3) & 1) * 8 + (lane & 7)) * OPITCH + (lane >> 4) * 16;
#pragma unroll
    for (int i = 0; i < 12; ++i)
      stsm_x4(addr + i * 32, pack_bf16(o[8 * i], o[8 * i + 1]), pack_bf16(o[8 * i + 2], o[8 * i + 3]),
              pack_bf16(o[8 * i + 4], o[8 * i + 5]), pack_bf16(o[8 * i + 6], o[8 * i + 7]));
  }
  named_bar(1 + w, 128);
  {
    const uint8_t* pS = sptr + (sS - sbase);
    uint4* dst = reinterpret_cast<uint4*>(out + (size_t)grow * C_);
#pragma unroll
    for (int it = 0; it < 12; ++it) {
      if (it < nit) {
        const int unit = it * 128 + t, row = unit / 24, u = unit - row * 24;
        const uint4 y = *reinterpret_cast<const uint4*>(pS + row * OPITCH + u * 16);
        dst[unit] = make_uint4(add_bf2(xv[it].x, y.x), add_bf2(xv[it].y, y.y), add_bf2(xv[it].z, y.z), add_bf2(xv[it].w, y.w));
      }
    }
  }
  PROF(2, w, 23);
}

}

extern "C" void kernel_launch(void* const* d_in, const int* in_sizes, int n_in, void* d_out, int out_size) {
  using namespace tsf;
  const __nv_bfloat16* x = (const __nv_bfloat16*)d_in[0];
  const __nv_bfloat16* wqkv_t = (const __nv_bfloat16*)d_in[1];
  const __nv_bfloat16* wo_t = (const __nv_bfloat16*)d_in[2];
  const __nv_bfloat16* wqkv_s = (const __nv_bfloat16*)d_in[3];
  const __nv_bfloat16* wo_s = (const __nv_bfloat16*)d_in[4];
  __nv_bfloat16* out = (__nv_bfloat16*)d_out;
  static bool init = false;
  if (!init) {
    cudaFuncSetAttribute(p1_kernel, cudaFuncAttributeMaxDynamicSharedMemorySize, P1_SMEM);
    cudaFuncSetAttribute(p2_kernel, cudaFuncAttributeMaxDynamicSharedMemorySize, P2_SMEM);
    cudaFuncSetAttribute(p1_kernel, cudaFuncAttributePreferredSharedMemoryCarveout, cudaSharedmemCarveoutMaxShared);
    cudaFuncSetAttribute(p2_kernel, cudaFuncAttributePreferredSharedMemoryCarveout, cudaSharedmemCarveoutMaxShared);
    init = true;
  }
  cudaStream_t st = cudaStreamPerThread;
  p1_kernel<<<120, 384, P1_SMEM, st>>>(x, wqkv_t, wo_t, wqkv_s, wo_s);
  cudaLaunchAttribute at[1];
  at[0].id = cudaLaunchAttributeProgrammaticStreamSerialization;
  at[0].val.programmaticStreamSerializationAllowed = 1;
  {
    cudaLaunchConfig_t cfg = {};
    cfg.gridDim = dim3(126); cfg.blockDim = dim3(384); cfg.dynamicSmemBytes = P2_SMEM; cfg.stream = st;
    cfg.attrs = at; cfg.numAttrs = 1;
    cudaLaunchKernelEx(&cfg, p2_kernel, out);
  }
}
```
